```python
import torch

def _softmax(x, axis=-1):
    return torch.softmax(x, dim=axis)

def _gelu(x):
    return torch.nn.functional.gelu(x, approximate='tanh')

def _silu(x):
    return torch.nn.functional.silu(x)

def _sigmoid(x):
    return torch.sigmoid(x)

def _layernorm(x, axis=-1, eps=1e-05):
    m = x.mean(dim=axis, keepdim=True)
    v = x.var(dim=axis, keepdim=True, unbiased=False)
    return (x - m) / torch.sqrt(v + eps)

def _scatter_add(tgt, idx, src, axis=0):
    return tgt.clone().index_add_(axis, idx, src)

def _segment_sum(src, seg, n):
    out = torch.zeros((n,) + src.shape[1:], dtype=src.dtype)
    return out.index_add_(0, seg, src)

def _pad(x, pw):
    flat = tuple((v for pair in reversed(pw) for v in pair))
    return torch.nn.functional.pad(x, flat)
kernel_name = 'standalone__tree_speculative_verify_tree_attention_over_candidate_token_tree__decode'

def setup_inputs():

    _w = lambda a: (lambda t: t.to(torch.bfloat16) if t.is_floating_point() else t)(torch.as_tensor(a))
    B, Hq, Hkv, T, C, D = (2, 32, 16, 1, 8192, 128)
    tree_mask = torch.zeros((B, T, T), dtype=float)
    for b in range(B):
        parent = torch.zeros(T, dtype=torch.int64)
        for i in range(1, T):
            parent[i] = int(torch.randint(0, i, (1,)).item())
        for i in range(T):
            j = i
            tree_mask[b, i, j] = 1.0
            while j > 0:
                j = parent[j]
                tree_mask[b, i, j] = 1.0
    return {'q': _w((lambda *s: torch.randn(*s, dtype=torch.bfloat16) * 0.8)(B, Hq, T, D)), 'k_cache': _w((lambda *s: torch.randn(*s, dtype=torch.bfloat16) * 0.8)(B, Hkv, C, D)), 'v_cache': _w((lambda *s: torch.randn(*s, dtype=torch.bfloat16) * 0.05)(B, Hkv, C, D)), 'k_tree': _w((lambda *s: torch.randn(*s, dtype=torch.bfloat16) * 0.8)(B, Hkv, T, D)), 'v_tree': _w((lambda *s: torch.randn(*s, dtype=torch.bfloat16) * 0.05)(B, Hkv, T, D)), 'tree_mask': _w(tree_mask)}

def reference(q, k_cache, v_cache, k_tree, v_tree, tree_mask):
    B, Hq, T, D = q.shape
    Hkv, C = (k_cache.shape[1], k_cache.shape[2])
    rep = Hq // Hkv
    kc = (lambda x, n, axis: torch.repeat_interleave(x, n, dim=axis))(k_cache, rep, axis=1)
    vc = (lambda x, n, axis: torch.repeat_interleave(x, n, dim=axis))(v_cache, rep, axis=1)
    kt = (lambda x, n, axis: torch.repeat_interleave(x, n, dim=axis))(k_tree, rep, axis=1)
    vt = (lambda x, n, axis: torch.repeat_interleave(x, n, dim=axis))(v_tree, rep, axis=1)
    k = torch.concatenate([kc, kt], axis=2)
    v = torch.concatenate([vc, vt], axis=2)
    scale = D ** (-0.5)
    scores = torch.einsum('bhqd,bhkd->bhqk', q, k) * scale
    ctx_mask = torch.ones((B, 1, T, C), dtype=scores.dtype)
    tm = tree_mask[:, None, :, :].clone()
    full_mask = torch.concatenate([ctx_mask, tm], axis=-1)
    scores = scores + (1.0 - full_mask) * -1000000000.0
    p = _softmax(scores, axis=-1)
    return torch.einsum('bhqk,bhkd->bhqd', p, v)
```

```cpp
#include <cuda_runtime.h>
#include <cuda_bf16.h>
#include <cuda.h>
#include <stdint.h>

namespace {

constexpr int kB = 2, kHkv = 16, kC = 8192, kD = 128;
constexpr int kPairs = kB * kHkv;
constexpr int kSplit = 4;
constexpr int kKeysPerCta = kC / kSplit;
constexpr int kTile = 64;
constexpr int kNW = kTile / 16;
constexpr int kNC = kNW * 32;
constexpr int kThreads = kNC + 32;
constexpr int kNS = 8;
constexpr int kNT = kKeysPerCta / kTile;
constexpr int kNL = 2 * kNT;
constexpr int kSlotBytes = kTile * kD * 2;
constexpr uint32_t kHalf = kTile * 128;
constexpr int kRedBytes = kNW * (1024 + 16);
constexpr int kSmemBytes = kNS * kSlotBytes + 1024   + kRedBytes + 2 * kNS * 8;
constexpr int kFreeLoads = 4;
constexpr int kMinInflight = 2;
constexpr int kOpenAt = kNT - 4;
constexpr float kScale = 0.08838834764831845f;
constexpr float kLog2e = 1.4426950408889634f;
static_assert(kNC == kD, "one consumer thread per output dim");

__device__ uint4 g_part[kPairs * kSplit * kD];

__device__ __forceinline__ uint32_t smem_u32(const void* p) { return (uint32_t)__cvta_generic_to_shared(p); }
__device__ __forceinline__ uint32_t timer_ns() { uint32_t t; asm volatile("mov.u32 %0, %globaltimer_lo;" : "=r"(t)); return t; }
__device__ __forceinline__ void mbar_init(uint32_t bar, uint32_t cnt) {
    asm volatile("mbarrier.init.shared::cta.b64 [%0], %1;" :: "r"(bar), "r"(cnt) : "memory");
}
__device__ __forceinline__ void mbar_expect_tx(uint32_t bar, uint32_t bytes) {
    asm volatile("mbarrier.arrive.expect_tx.shared::cta.b64 _, [%0], %1;" :: "r"(bar), "r"(bytes) : "memory");
}
__device__ __forceinline__ void mbar_arrive(uint32_t bar) {
    asm volatile("mbarrier.arrive.shared::cta.b64 _, [%0];" :: "r"(bar) : "memory");
}
__device__ __forceinline__ bool mbar_test(uint32_t bar, uint32_t parity) {
    uint32_t ok;
    asm volatile("{\n.reg .pred p;\nmbarrier.test_wait.parity.shared::cta.b64 p, [%1], %2;\nselp.u32 %0, 1, 0, p;\n}"
                 : "=r"(ok) : "r"(bar), "r"(parity) : "memory");
    return ok != 0;
}
__device__ __forceinline__ void mbar_wait(uint32_t bar, uint32_t parity) {
    asm volatile(
        "{\n"
        ".reg .pred p, q;\n"
        ".reg .u32 c;\n"
        "mov.u32 c, 0;\n"
        "LAB_WAIT:\n"
        "mbarrier.try_wait.parity.shared::cta.b64 p, [%0], %1;\n"
        "@p bra LAB_DONE;\n"
        "add.u32 c, c, 1;\n"
        "setp.lt.u32 q, c, 0x1000000;\n"
        "@q bra LAB_WAIT;\n"
        "trap;\n"
        "LAB_DONE:\n"
        "}\n" :: "r"(bar), "r"(parity) : "memory");
}
__device__ __forceinline__ void tma_tile(uint32_t dst, const CUtensorMap* tm, int row, uint32_t bar) {
    asm volatile("cp.async.bulk.tensor.3d.shared::cluster.global.mbarrier::complete_tx::bytes [%0], [%1, {%3, %4, %3}], [%2];"
                 :: "r"(dst), "l"(tm), "r"(bar), "r"(0), "r"(row) : "memory");
}
__device__ __forceinline__ void ldsm4(uint32_t (&r)[4], uint32_t addr) {
    asm volatile("ldmatrix.sync.aligned.m8n8.x4.shared.b16 {%0,%1,%2,%3}, [%4];"
                 : "=r"(r[0]), "=r"(r[1]), "=r"(r[2]), "=r"(r[3]) : "r"(addr));
}
__device__ __forceinline__ void ldsm4t(uint32_t (&r)[4], uint32_t addr) {
    asm volatile("ldmatrix.sync.aligned.m8n8.x4.trans.shared.b16 {%0,%1,%2,%3}, [%4];"
                 : "=r"(r[0]), "=r"(r[1]), "=r"(r[2]), "=r"(r[3]) : "r"(addr));
}
__device__ __forceinline__ void mma16816(float (&d)[4], uint32_t a0, uint32_t a1, uint32_t a2, uint32_t a3, uint32_t b0, uint32_t b1) {
    asm volatile("mma.sync.aligned.m16n8k16.row.col.f32.bf16.bf16.f32 {%0,%1,%2,%3}, {%4,%5,%6,%7}, {%8,%9}, {%0,%1,%2,%3};"
                 : "+f"(d[0]), "+f"(d[1]), "+f"(d[2]), "+f"(d[3]) : "r"(a0), "r"(a1), "r"(a2), "r"(a3), "r"(b0), "r"(b1));
}
__device__ __forceinline__ float ex2(float x) { float y; asm("ex2.approx.ftz.f32 %0, %1;" : "=f"(y) : "f"(x)); return y; }
__device__ __forceinline__ float lg2(float x) { float y; asm("lg2.approx.ftz.f32 %0, %1;" : "=f"(y) : "f"(x)); return y; }
__device__ __forceinline__ float rcp(float x) { float y; asm("rcp.approx.ftz.f32 %0, %1;" : "=f"(y) : "f"(x)); return y; }
__device__ __forceinline__ uint32_t pack_bf16(float lo, float hi) {
    uint32_t r; asm("cvt.rn.bf16x2.f32 %0, %1, %2;" : "=r"(r) : "f"(hi), "f"(lo)); return r;
}
__device__ __forceinline__ float bf_lo(uint32_t v) { return __uint_as_float(v << 16); }
__device__ __forceinline__ float bf_hi(uint32_t v) { return __uint_as_float(v & 0xffff0000u); }
__device__ __forceinline__ float bf_round(float x) { return __bfloat162float(__float2bfloat16(x)); }
__device__ __forceinline__ void scale_scores(float& a, float& b) {
    uint32_t r = pack_bf16(a, b);
    r = pack_bf16(bf_lo(r) * kScale, bf_hi(r) * kScale);
    a = bf_lo(r); b = bf_hi(r);
}
__device__ __forceinline__ void st_rec(uint4* p, uint64_t a, uint64_t b) {
    asm volatile("st.relaxed.gpu.global.v2.b64 [%0], {%1, %2};" :: "l"(p), "l"(a), "l"(b) : "memory");
}
__device__ __forceinline__ void ld_rec_if(uint64_t& a, uint64_t& b, const uint4* p, bool pred) {
    asm volatile("{\n.reg .pred p;\nsetp.ne.u32 p, %3, 0;\n@p ld.relaxed.gpu.global.v2.b64 {%0, %1}, [%2];\n}"
                 : "+l"(a), "+l"(b) : "l"(p), "r"((uint32_t)pred) : "memory");
}
__device__ __forceinline__ uint64_t rec_word(float o, float lse) {
    uint32_t u = __float_as_uint(lse);
    if (u == 0u) u = 0x80000000u;
    return ((uint64_t)u << 32) | __float_as_uint(o);
}
__device__ __forceinline__ float rec_o(uint64_t w) { return __uint_as_float((uint32_t)w); }
__device__ __forceinline__ float rec_lse(uint64_t w) { return __uint_as_float((uint32_t)(w >> 32)); }

__global__ void __launch_bounds__(kThreads, 1)
tree_attn_decode_kernel(const __grid_constant__ CUtensorMap tmK, const __grid_constant__ CUtensorMap tmV,
                        const __nv_bfloat16* __restrict__ q, const __nv_bfloat16* __restrict__ k_tree,
                        const __nv_bfloat16* __restrict__ v_tree, const __nv_bfloat16* __restrict__ mask,
                        __nv_bfloat16* __restrict__ out, uint4* __restrict__ part, int pace_off_ns, int pace_tau_q8)
{
    extern __shared__ uint8_t smem_raw[];
    const uint32_t sbase = (smem_u32(smem_raw) + 1023) & ~1023u;
    const uint32_t red = sbase + kNS * kSlotBytes;
    const uint32_t full = red + kRedBytes;
    const uint32_t empty = full + kNS * 8;
    const int row0 = blockIdx.x * kKeysPerCta;

    uint32_t t0 = 0;
    if (threadIdx.x == kNC) {
        t0 = timer_ns();
#pragma unroll
        for (int s = 0; s < kNS; s++) mbar_init(full + s * 8, 1);
        asm volatile("fence.mbarrier_init.release.cluster;" ::: "memory");
        mbar_expect_tx(full, kSlotBytes);
        tma_tile(sbase, &tmK, row0, full);
        mbar_expect_tx(full + 8, kSlotBytes);
        tma_tile(sbase + kSlotBytes, &tmK, row0 + kTile, full + 8);
        mbar_expect_tx(full + 16, kSlotBytes);
        tma_tile(sbase + 2 * kSlotBytes, &tmV, row0, full + 16);
#pragma unroll
        for (int s = 0; s < kNS; s++) mbar_init(empty + s * 8, kNW);
    }
    const int warp = threadIdx.x >> 5, lane = threadIdx.x & 31;

    if (warp == kNW) {
        __syncwarp();
        asm volatile("bar.arrive 1, %0;" :: "n"(kThreads) : "memory");
        if (lane == 0) {
#pragma unroll 1
            for (int i = 3; i < kNL; i++) {
                const int s = i % kNS;
                mbar_wait(empty + s * 8, ((i / kNS) & 1) ^ 1);
                if (i >= kFreeLoads) {
                    const uint32_t due = (uint32_t)(pace_off_ns + (((i - kFreeLoads) * pace_tau_q8) >> 8));
                    const int j = i - kMinInflight;
                    while (timer_ns() - t0 < due && !mbar_test(full + (j % kNS) * 8, (j / kNS) & 1)) { }
                }
                const bool is_k = (i & 1) && i != kNL - 1;
                const int tile = is_k ? (i + 1) >> 1 : (i - 1) >> 1;
                mbar_expect_tx(full + s * 8, kSlotBytes);
                tma_tile(sbase + s * kSlotBytes, is_k ? &tmK : &tmV, row0 + tile * kTile, full + s * 8);
            }
        }
        return;
    }

    const int tid = threadIdx.x;
    const int g = lane >> 2, t = lane & 3;
    const int pair = blockIdx.x >> 2, split = blockIdx.x & 3;
    const bool merger = (split == kSplit - 1);

    uint32_t qa[8][2];
    {
        const uint32_t* qp = reinterpret_cast<const uint32_t*>(q + (size_t)(pair * 2 + (g & 1)) * kD);
#pragma unroll
        for (int j = 0; j < 8; j++) { qa[j][0] = __ldg(qp + j * 8 + t); qa[j][1] = __ldg(qp + j * 8 + 4 + t); }
    }
    uint4* pp = part + (size_t)(merger ? pair * kSplit : blockIdx.x) * kD + tid;
    __nv_bfloat16* op = out + (size_t)pair * 2 * kD + tid;
    asm volatile("" : "+l"(pp), "+l"(op));

    float acc[8][4];
    float m = -INFINITY, l = 0.f;
#pragma unroll
    for (int j = 0; j < 8; j++) { acc[j][0] = acc[j][1] = acc[j][2] = acc[j][3] = 0.f; }
    if (merger && warp == 0) {
        const uint32_t* kp = reinterpret_cast<const uint32_t*>(k_tree + (size_t)pair * kD);
        const __nv_bfloat16* vp = v_tree + (size_t)pair * kD;
        float s4[4] = {0.f, 0.f, 0.f, 0.f};
#pragma unroll
        for (int j = 0; j < 8; j++) {
            mma16816(s4, qa[j][0], 0u, qa[j][1], 0u, __ldg(kp + j * 8 + t), __ldg(kp + j * 8 + 4 + t));
            acc[j][0] = acc[j][1] = __bfloat162float(vp[j * 16 + g]);
            acc[j][2] = acc[j][3] = __bfloat162float(vp[j * 16 + 8 + g]);
        }
        scale_scores(s4[0], s4[1]);
        const float keep = __bfloat162float(mask[pair / kHkv]);
        m = bf_round(s4[0] + bf_round(bf_round(1.0f - keep) * -1000000000.0f));
        l = (t == 0) ? 1.f : 0.f;
    }

    const int r7 = lane & 7, mi = lane >> 3;
    const uint32_t ka0 = sbase + (uint32_t)(warp * 16 + r7) * 128 + ((mi ^ r7) << 4);
    const uint32_t ka1 = sbase + (uint32_t)(warp * 16 + r7) * 128 + (((4 + mi) ^ r7) << 4);
    uint32_t va[4];
#pragma unroll
    for (int jj = 0; jj < 4; jj++)
        va[jj] = sbase + (uint32_t)(warp * 16 + (mi >> 1) * 8 + r7) * 128 + (((jj * 2 + (mi & 1)) ^ r7) << 4);

    asm volatile("bar.sync 1, %0;" :: "n"(kThreads) : "memory");

    int s = 0, ph = 0;
    auto release = [&]() {
        __syncwarp();
        if (lane == 0) mbar_arrive(empty + s * 8);
        if (++s == kNS) { s = 0; ph ^= 1; }
    };
    auto scale_acc = [&](float f) {
        const float fo = __shfl_xor_sync(0xffffffffu, f, 4);
        const float f0 = (g & 1) ? fo : f, f1 = (g & 1) ? f : fo;
#pragma unroll
        for (int j = 0; j < 8; j++) { acc[j][0] *= f0; acc[j][1] *= f1; acc[j][2] *= f0; acc[j][3] *= f1; }
    };
    auto qk = [&](float (&sv)[4]) {
        uint32_t a0 = ka0 + s * kSlotBytes, a1 = ka1 + s * kSlotBytes;
        asm volatile("" : "+r"(a0), "+r"(a1));
        mbar_wait(full + s * 8, ph);
        float sc[2][2][4];
#pragma unroll
        for (int u = 0; u < 2; u++)
#pragma unroll
            for (int c = 0; c < 2; c++) sc[u][c][0] = sc[u][c][1] = sc[u][c][2] = sc[u][c][3] = 0.f;
#pragma unroll
        for (int qd = 0; qd < 4; qd++) {
#pragma unroll
            for (int u = 0; u < 2; u++) {
                uint32_t r[4];
                ldsm4(r, ((qd & 1) ? a1 : a0) + u * 1024 + (qd >> 1) * kHalf);
                mma16816(sc[u][0], qa[2 * qd][0], 0u, qa[2 * qd][1], 0u, r[0], r[1]);
                mma16816(sc[u][1], qa[2 * qd + 1][0], 0u, qa[2 * qd + 1][1], 0u, r[2], r[3]);
            }
        }
        release();
        sv[0] = sc[0][0][0] + sc[0][1][0]; sv[1] = sc[0][0][1] + sc[0][1][1];
        sv[2] = sc[1][0][0] + sc[1][1][0]; sv[3] = sc[1][0][1] + sc[1][1][1];
        scale_scores(sv[0], sv[1]);
        scale_scores(sv[2], sv[3]);
        float mx = fmaxf(fmaxf(sv[0], sv[1]), fmaxf(sv[2], sv[3]));
        mx = fmaxf(mx, __shfl_xor_sync(0xffffffffu, mx, 1));
        mx = fmaxf(mx, __shfl_xor_sync(0xffffffffu, mx, 2));
        if (__any_sync(0xffffffffu, mx > m)) {
            const float mn = fmaxf(m, mx);
            const float f = ex2((m - mn) * kLog2e);
            m = mn; l *= f;
            scale_acc(f);
        }
    };
    auto probs = [&](const float (&sv)[4], float (&p)[4]) {
        const float ml = m * kLog2e;
#pragma unroll
        for (int x = 0; x < 4; x++) p[x] = ex2(fmaf(sv[x], kLog2e, -ml));
        l += (p[0] + p[1]) + (p[2] + p[3]);
    };
    auto pv = [&](uint32_t b0, uint32_t b1) {
        uint32_t a[4];
#pragma unroll
        for (int jj = 0; jj < 4; jj++) a[jj] = va[jj] + s * kSlotBytes;
        asm volatile("" : "+r"(a[0]), "+r"(a[1]), "+r"(a[2]), "+r"(a[3]));
        mbar_wait(full + s * 8, ph);
#pragma unroll
        for (int j = 0; j < 8; j++) {
            uint32_t r[4];
            ldsm4t(r, a[j & 3] + (j >> 2) * kHalf);
            mma16816(acc[j], r[0], r[1], r[2], r[3], b0, b1);
        }
    };

    float e0 = 0.f, e1 = 0.f;
    float scur[4], snxt[4], p[4];
    uint32_t bl0 = 0, bl1 = 0;
    qk(scur);
#pragma unroll 1
    for (int n = 0; n < kNT - 1; n++) {
        if (n == kOpenAt && !merger) st_rec(pp, 0ull, 0ull);
        qk(snxt);
        probs(scur, p);
        if (n == kNT - 2) {
            float p2[4];
            probs(snxt, p2);
            float lr = l + __shfl_xor_sync(0xffffffffu, l, 1);
            lr += __shfl_xor_sync(0xffffffffu, lr, 2);
            if (t == 0 && g < 2)
                asm volatile("st.shared.v2.f32 [%0], {%1,%2};" :: "r"(red + kNW * 1024 + warp * 16 + g * 8), "f"(m), "f"(lr) : "memory");
            asm volatile("bar.sync 2, %0;" :: "n"(kNC) : "memory");
            float mm[kNW][4];
            float M0 = -INFINITY, M1 = -INFINITY;
#pragma unroll
            for (int w = 0; w < kNW; w++) {
                asm volatile("ld.shared.v4.f32 {%0,%1,%2,%3}, [%4];"
                             : "=f"(mm[w][0]), "=f"(mm[w][1]), "=f"(mm[w][2]), "=f"(mm[w][3]) : "r"(red + kNW * 1024 + w * 16));
                M0 = fmaxf(M0, mm[w][0]); M1 = fmaxf(M1, mm[w][2]);
            }
            float L0 = 0.f, L1 = 0.f;
#pragma unroll
            for (int w = 0; w < kNW; w++) {
                L0 = fmaf(ex2((mm[w][0] - M0) * kLog2e), mm[w][1], L0);
                L1 = fmaf(ex2((mm[w][2] - M1) * kLog2e), mm[w][3], L1);
            }
            e0 = fmaf(M0, kLog2e, lg2(L0)); e1 = fmaf(M1, kLog2e, lg2(L1));
            const float f = ex2((m - ((g & 1) ? M1 : M0)) * kLog2e) * rcp((g & 1) ? L1 : L0);
            scale_acc(f);
#pragma unroll
            for (int x = 0; x < 4; x++) { p[x] *= f; p2[x] *= f; }
            bl0 = pack_bf16(p2[0], p2[1]); bl1 = pack_bf16(p2[2], p2[3]);
        }
        pv(pack_bf16(p[0], p[1]), pack_bf16(p[2], p[3]));
        release();
#pragma unroll
        for (int x = 0; x < 4; x++) scur[x] = snxt[x];
    }
    uint32_t sta = red + warp * 1024 + g * 16;
    uint32_t lda = red + (((tid >> 4) * 8 + (tid & 7)) * 16) + ((tid >> 3) & 1) * 8;
    asm volatile("" : "+r"(sta), "+r"(lda));
    pv(bl0, bl1);

    uint64_t ra[kSplit - 1], rb[kSplit - 1];
#pragma unroll
    for (int x = 0; x < kSplit - 1; x++) { ra[x] = rb[x] = 0ull; ld_rec_if(ra[x], rb[x], pp + x * kD, merger); }
    if (t == 0) {
#pragma unroll
        for (int j = 0; j < 8; j++)
            asm volatile("st.shared.v4.f32 [%0], {%1,%2,%3,%4};"
                         :: "r"(sta + j * 128), "f"(acc[j][0]), "f"(acc[j][1]), "f"(acc[j][2]), "f"(acc[j][3]) : "memory");
    }
    asm volatile("bar.sync 2, %0;" :: "n"(kNC) : "memory");
    float av[kNW][2];
#pragma unroll
    for (int w = 0; w < kNW; w++)
        asm volatile("ld.shared.v2.f32 {%0,%1}, [%2];" : "=f"(av[w][0]), "=f"(av[w][1]) : "r"(lda + w * 1024));
    const float o0 = (av[0][0] + av[1][0]) + (av[2][0] + av[3][0]);
    const float o1 = (av[0][1] + av[1][1]) + (av[2][1] + av[3][1]);
    if (!merger) {
        st_rec(pp, rec_word(o0, e0), rec_word(o1, e1));
        return;
    }
#pragma unroll 1
    for (int it = 0;; it++) {
        bool miss[kSplit - 1];
#pragma unroll
        for (int x = 0; x < kSplit - 1; x++) miss[x] = (ra[x] >> 32) == 0 || (rb[x] >> 32) == 0;
        if (!(miss[0] || miss[1] || miss[2])) break;
        if (it > (1 << 22)) __trap();
#pragma unroll
        for (int x = 0; x < kSplit - 1; x++) ld_rec_if(ra[x], rb[x], pp + x * kD, miss[x]);
    }
    float E0 = e0, E1 = e1;
#pragma unroll
    for (int x = 0; x < kSplit - 1; x++) { E0 = fmaxf(E0, rec_lse(ra[x])); E1 = fmaxf(E1, rec_lse(rb[x])); }
    float w0 = ex2(e0 - E0), w1 = ex2(e1 - E1);
    float n0 = w0 * o0, n1 = w1 * o1;
#pragma unroll
    for (int x = 0; x < kSplit - 1; x++) {
        const float a = ex2(rec_lse(ra[x]) - E0), b = ex2(rec_lse(rb[x]) - E1);
        w0 += a; w1 += b;
        n0 = fmaf(a, rec_o(ra[x]), n0); n1 = fmaf(b, rec_o(rb[x]), n1);
    }
    op[0] = __float2bfloat16(n0 * rcp(w0));
    op[kD] = __float2bfloat16(n1 * rcp(w1));
#pragma unroll
    for (int x = 0; x < kSplit - 1; x++) st_rec(pp + x * kD, 0ull, 0ull);
}

typedef CUresult (*EncodeTiledFn)(CUtensorMap*, CUtensorMapDataType, cuuint32_t, void*, const cuuint64_t*, const cuuint64_t*,
                                  const cuuint32_t*, const cuuint32_t*, CUtensorMapInterleave, CUtensorMapSwizzle,
                                  CUtensorMapL2promotion, CUtensorMapFloatOOBfill);

CUtensorMap make_kv_map(EncodeTiledFn encode, void* base) {
    CUtensorMap m;
    const cuuint64_t dims[3] = {64, (cuuint64_t)kPairs * kC, 2};
    const cuuint64_t strides[2] = {256, 128};
    const cuuint32_t box[3] = {64, (cuuint32_t)kTile, 2};
    const cuuint32_t elem[3] = {1, 1, 1};
    encode(&m, CU_TENSOR_MAP_DATA_TYPE_BFLOAT16, 3, base, dims, strides, box, elem, CU_TENSOR_MAP_INTERLEAVE_NONE,
           CU_TENSOR_MAP_SWIZZLE_128B, CU_TENSOR_MAP_L2_PROMOTION_L2_256B, CU_TENSOR_MAP_FLOAT_OOB_FILL_NONE);
    return m;
}

}

extern "C" void kernel_launch(void* const* d_in, const int* in_sizes, int n_in, void* d_out, int out_size) {
    (void)in_sizes; (void)n_in; (void)out_size;
    static EncodeTiledFn encode = nullptr;
    static void* part = nullptr;
    static int pace_off_ns = 0, pace_tau_q8 = 0;
    if (!encode) {
        cudaDriverEntryPointQueryResult qr;
        cudaGetDriverEntryPoint("cuTensorMapEncodeTiled", (void**)&encode, cudaEnableDefault, &qr);
        cudaFuncSetAttribute(tree_attn_decode_kernel, cudaFuncAttributeMaxDynamicSharedMemorySize, kSmemBytes);
        cudaGetSymbolAddress(&part, g_part);
        int dev = 0, mem_khz = 0, bus_bits = 0;
        cudaGetDevice(&dev);
        cudaDeviceGetAttribute(&mem_khz, cudaDevAttrMemoryClockRate, dev);
        cudaDeviceGetAttribute(&bus_bits, cudaDevAttrGlobalMemoryBusWidth, dev);
        const double bytes_per_ns = 2.0 * mem_khz * 1e-6 * bus_bits / 8.0;
        if (bytes_per_ns > 0.0) {
            const double tau = (double)kPairs * kSplit * kSlotBytes / (0.976 * bytes_per_ns);
            pace_tau_q8 = (int)(tau * 256.0);
            pace_off_ns = (int)(800.0 + (kFreeLoads + 1) * tau - 2000.0);
        }
    }
    const CUtensorMap tmK = make_kv_map(encode, d_in[1]);
    const CUtensorMap tmV = make_kv_map(encode, d_in[2]);
    tree_attn_decode_kernel<<<kPairs * kSplit, kThreads, kSmemBytes>>>(
        tmK, tmV, (const __nv_bfloat16*)d_in[0], (const __nv_bfloat16*)d_in[3], (const __nv_bfloat16*)d_in[4],
        (const __nv_bfloat16*)d_in[5], (__nv_bfloat16*)d_out, (uint4*)part, pace_off_ns, pace_tau_q8);
}
```

```cpp
#include <cuda_runtime.h>
#include <cuda_bf16.h>
#include <cuda.h>
#include <stdint.h>

namespace {

constexpr int kB = 2, kHkv = 16, kC = 8192, kD = 128;
constexpr int kPairs = kB * kHkv;
constexpr int kSplit = 4;
constexpr int kKeysPerCta = kC / kSplit;
constexpr int kTile = 64;
constexpr int kNW = kTile / 16;
constexpr int kNC = kNW * 32;
constexpr int kThreads = kNC + 32;
constexpr int kNS = 8;
constexpr int kNT = kKeysPerCta / kTile;
constexpr int kNL = 2 * kNT;
constexpr int kSlotBytes = kTile * kD * 2;
constexpr uint32_t kHalf = kTile * 128;
constexpr int kRedBytes = kNW * (1024 + 16);
constexpr int kSmemBytes = kNS * kSlotBytes + 1024   + kRedBytes + 2 * kNS * 8;
constexpr int kFreeLoads = 4;
constexpr int kMinInflight = 2;
constexpr int kMergerLagNs = 250;
constexpr int kOpenAt = kNT - 4;
constexpr float kScale = 0.08838834764831845f;
constexpr float kLog2e = 1.4426950408889634f;
static_assert(kNC == kD, "one consumer thread per output dim");

__device__ uint4 g_part[kPairs * kSplit * kD];

__device__ __forceinline__ uint32_t smem_u32(const void* p) { return (uint32_t)__cvta_generic_to_shared(p); }
__device__ __forceinline__ uint32_t timer_ns() { uint32_t t; asm volatile("mov.u32 %0, %globaltimer_lo;" : "=r"(t)); return t; }
__device__ __forceinline__ void mbar_init(uint32_t bar, uint32_t cnt) {
    asm volatile("mbarrier.init.shared::cta.b64 [%0], %1;" :: "r"(bar), "r"(cnt) : "memory");
}
__device__ __forceinline__ void mbar_expect_tx(uint32_t bar, uint32_t bytes) {
    asm volatile("mbarrier.arrive.expect_tx.shared::cta.b64 _, [%0], %1;" :: "r"(bar), "r"(bytes) : "memory");
}
__device__ __forceinline__ void mbar_arrive(uint32_t bar) {
    asm volatile("mbarrier.arrive.shared::cta.b64 _, [%0];" :: "r"(bar) : "memory");
}
__device__ __forceinline__ bool mbar_test(uint32_t bar, uint32_t parity) {
    uint32_t ok;
    asm volatile("{\n.reg .pred p;\nmbarrier.test_wait.parity.shared::cta.b64 p, [%1], %2;\nselp.u32 %0, 1, 0, p;\n}"
                 : "=r"(ok) : "r"(bar), "r"(parity) : "memory");
    return ok != 0;
}
__device__ __forceinline__ void mbar_wait(uint32_t bar, uint32_t parity) {
    asm volatile(
        "{\n"
        ".reg .pred p, q;\n"
        ".reg .u32 c;\n"
        "mov.u32 c, 0;\n"
        "LAB_WAIT:\n"
        "mbarrier.try_wait.parity.shared::cta.b64 p, [%0], %1;\n"
        "@p bra LAB_DONE;\n"
        "add.u32 c, c, 1;\n"
        "setp.lt.u32 q, c, 0x1000000;\n"
        "@q bra LAB_WAIT;\n"
        "trap;\n"
        "LAB_DONE:\n"
        "}\n" :: "r"(bar), "r"(parity) : "memory");
}
__device__ __forceinline__ void tma_tile(uint32_t dst, const CUtensorMap* tm, int row, uint32_t bar) {
    asm volatile("cp.async.bulk.tensor.3d.shared::cluster.global.mbarrier::complete_tx::bytes [%0], [%1, {%3, %4, %3}], [%2];"
                 :: "r"(dst), "l"(tm), "r"(bar), "r"(0), "r"(row) : "memory");
}
__device__ __forceinline__ void ldsm4(uint32_t (&r)[4], uint32_t addr) {
    asm volatile("ldmatrix.sync.aligned.m8n8.x4.shared.b16 {%0,%1,%2,%3}, [%4];"
                 : "=r"(r[0]), "=r"(r[1]), "=r"(r[2]), "=r"(r[3]) : "r"(addr));
}
__device__ __forceinline__ void ldsm4t(uint32_t (&r)[4], uint32_t addr) {
    asm volatile("ldmatrix.sync.aligned.m8n8.x4.trans.shared.b16 {%0,%1,%2,%3}, [%4];"
                 : "=r"(r[0]), "=r"(r[1]), "=r"(r[2]), "=r"(r[3]) : "r"(addr));
}
__device__ __forceinline__ void mma16816(float (&d)[4], uint32_t a0, uint32_t a1, uint32_t a2, uint32_t a3, uint32_t b0, uint32_t b1) {
    asm volatile("mma.sync.aligned.m16n8k16.row.col.f32.bf16.bf16.f32 {%0,%1,%2,%3}, {%4,%5,%6,%7}, {%8,%9}, {%0,%1,%2,%3};"
                 : "+f"(d[0]), "+f"(d[1]), "+f"(d[2]), "+f"(d[3]) : "r"(a0), "r"(a1), "r"(a2), "r"(a3), "r"(b0), "r"(b1));
}
__device__ __forceinline__ float ex2(float x) { float y; asm("ex2.approx.ftz.f32 %0, %1;" : "=f"(y) : "f"(x)); return y; }
__device__ __forceinline__ float lg2(float x) { float y; asm("lg2.approx.ftz.f32 %0, %1;" : "=f"(y) : "f"(x)); return y; }
__device__ __forceinline__ float rcp(float x) { float y; asm("rcp.approx.ftz.f32 %0, %1;" : "=f"(y) : "f"(x)); return y; }
__device__ __forceinline__ uint32_t pack_bf16(float lo, float hi) {
    uint32_t r; asm("cvt.rn.bf16x2.f32 %0, %1, %2;" : "=r"(r) : "f"(hi), "f"(lo)); return r;
}
__device__ __forceinline__ float bf_lo(uint32_t v) { return __uint_as_float(v << 16); }
__device__ __forceinline__ float bf_hi(uint32_t v) { return __uint_as_float(v & 0xffff0000u); }
__device__ __forceinline__ float bf_round(float x) { return __bfloat162float(__float2bfloat16(x)); }
__device__ __forceinline__ void scale_scores(float& a, float& b) {
    uint32_t r = pack_bf16(a, b);
    r = pack_bf16(bf_lo(r) * kScale, bf_hi(r) * kScale);
    a = bf_lo(r); b = bf_hi(r);
}
__device__ __forceinline__ void st_rec(uint4* p, uint64_t a, uint64_t b) {
    asm volatile("st.relaxed.gpu.global.v2.b64 [%0], {%1, %2};" :: "l"(p), "l"(a), "l"(b) : "memory");
}
__device__ __forceinline__ void ld_rec_if(uint64_t& a, uint64_t& b, const uint4* p, bool pred) {
    asm volatile("{\n.reg .pred p;\nsetp.ne.u32 p, %3, 0;\n@p ld.relaxed.gpu.global.v2.b64 {%0, %1}, [%2];\n}"
                 : "+l"(a), "+l"(b) : "l"(p), "r"((uint32_t)pred) : "memory");
}
__device__ __forceinline__ uint64_t rec_word(float o, float lse) {
    uint32_t u = __float_as_uint(lse);
    if (u == 0u) u = 0x80000000u;
    return ((uint64_t)u << 32) | __float_as_uint(o);
}
__device__ __forceinline__ float rec_o(uint64_t w) { return __uint_as_float((uint32_t)w); }
__device__ __forceinline__ float rec_lse(uint64_t w) { return __uint_as_float((uint32_t)(w >> 32)); }

__global__ void __launch_bounds__(kThreads, 1)
tree_attn_decode_kernel(const __grid_constant__ CUtensorMap tmK, const __grid_constant__ CUtensorMap tmV,
                        const __nv_bfloat16* __restrict__ q, const __nv_bfloat16* __restrict__ k_tree,
                        const __nv_bfloat16* __restrict__ v_tree, const __nv_bfloat16* __restrict__ mask,
                        __nv_bfloat16* __restrict__ out, uint4* __restrict__ part,
                        const __nv_bfloat16* __restrict__ k_cache, const __nv_bfloat16* __restrict__ v_cache,
                        int pace_off_ns, int pace_tau_q8)
{
    const int row0 = blockIdx.x * kKeysPerCta;
    if (threadIdx.x == 0) {
        asm volatile("cp.async.bulk.prefetch.L2.global [%0], %1;" :: "l"(k_cache + (size_t)row0 * kD), "n"(2 * kSlotBytes) : "memory");
        asm volatile("cp.async.bulk.prefetch.L2.global [%0], %1;" :: "l"(v_cache + (size_t)row0 * kD), "n"(kSlotBytes) : "memory");
    }
    extern __shared__ uint8_t smem_raw[];
    const uint32_t sbase = (smem_u32(smem_raw) + 1023) & ~1023u;
    const uint32_t red = sbase + kNS * kSlotBytes;
    const uint32_t full = red + kRedBytes;
    const uint32_t empty = full + kNS * 8;

    uint32_t t0 = 0;
    if (threadIdx.x == kNC) {
        t0 = timer_ns();
#pragma unroll
        for (int s = 0; s < kNS; s++) mbar_init(full + s * 8, 1);
        asm volatile("fence.mbarrier_init.release.cluster;" ::: "memory");
        mbar_expect_tx(full, kSlotBytes);
        tma_tile(sbase, &tmK, row0, full);
        mbar_expect_tx(full + 8, kSlotBytes);
        tma_tile(sbase + kSlotBytes, &tmK, row0 + kTile, full + 8);
        mbar_expect_tx(full + 16, kSlotBytes);
        tma_tile(sbase + 2 * kSlotBytes, &tmV, row0, full + 16);
#pragma unroll
        for (int s = 0; s < kNS; s++) mbar_init(empty + s * 8, kNW);
    }
    const int warp = threadIdx.x >> 5, lane = threadIdx.x & 31;

    if (warp == kNW) {
        __syncwarp();
        asm volatile("bar.arrive 1, %0;" :: "n"(kThreads) : "memory");
        if (lane == 0) {
            const int off = pace_off_ns + (((blockIdx.x & 3) == kSplit - 1) ? kMergerLagNs : 0);
#pragma unroll 1
            for (int i = 3; i < kNL; i++) {
                const int s = i % kNS;
                mbar_wait(empty + s * 8, ((i / kNS) & 1) ^ 1);
                if (i >= kFreeLoads) {
                    const uint32_t due = (uint32_t)(off + (((i - kFreeLoads) * pace_tau_q8) >> 8));
                    const int j = i - kMinInflight;
                    while (timer_ns() - t0 < due && !mbar_test(full + (j % kNS) * 8, (j / kNS) & 1)) { }
                }
                const bool is_k = (i & 1) && i != kNL - 1;
                const int tile = is_k ? (i + 1) >> 1 : (i - 1) >> 1;
                mbar_expect_tx(full + s * 8, kSlotBytes);
                tma_tile(sbase + s * kSlotBytes, is_k ? &tmK : &tmV, row0 + tile * kTile, full + s * 8);
            }
        }
        return;
    }

    const int tid = threadIdx.x;
    const int g = lane >> 2, t = lane & 3;
    const int pair = blockIdx.x >> 2, split = blockIdx.x & 3;
    const bool merger = (split == kSplit - 1);

    uint32_t qa[8][2];
    {
        const uint32_t* qp = reinterpret_cast<const uint32_t*>(q + (size_t)(pair * 2 + (g & 1)) * kD);
#pragma unroll
        for (int j = 0; j < 8; j++) { qa[j][0] = __ldg(qp + j * 8 + t); qa[j][1] = __ldg(qp + j * 8 + 4 + t); }
    }
    uint4* pp = part + (size_t)(merger ? pair * kSplit : blockIdx.x) * kD + tid;
    __nv_bfloat16* op = out + (size_t)pair * 2 * kD + tid;
    asm volatile("" : "+l"(pp), "+l"(op));

    float acc[8][4];
    float m = -INFINITY, l = 0.f;
#pragma unroll
    for (int j = 0; j < 8; j++) { acc[j][0] = acc[j][1] = acc[j][2] = acc[j][3] = 0.f; }
    if (merger && warp == 0) {
        const uint32_t* kp = reinterpret_cast<const uint32_t*>(k_tree + (size_t)pair * kD);
        const __nv_bfloat16* vp = v_tree + (size_t)pair * kD;
        float s4[4] = {0.f, 0.f, 0.f, 0.f};
#pragma unroll
        for (int j = 0; j < 8; j++) {
            mma16816(s4, qa[j][0], 0u, qa[j][1], 0u, __ldg(kp + j * 8 + t), __ldg(kp + j * 8 + 4 + t));
            acc[j][0] = acc[j][1] = __bfloat162float(vp[j * 16 + g]);
            acc[j][2] = acc[j][3] = __bfloat162float(vp[j * 16 + 8 + g]);
        }
        scale_scores(s4[0], s4[1]);
        const float keep = __bfloat162float(mask[pair / kHkv]);
        m = bf_round(s4[0] + bf_round(bf_round(1.0f - keep) * -1000000000.0f));
        l = (t == 0) ? 1.f : 0.f;
    }

    const int r7 = lane & 7, mi = lane >> 3;
    const uint32_t ka0 = sbase + (uint32_t)(warp * 16 + r7) * 128 + ((mi ^ r7) << 4);
    const uint32_t ka1 = sbase + (uint32_t)(warp * 16 + r7) * 128 + (((4 + mi) ^ r7) << 4);
    uint32_t va[4];
#pragma unroll
    for (int jj = 0; jj < 4; jj++)
        va[jj] = sbase + (uint32_t)(warp * 16 + (mi >> 1) * 8 + r7) * 128 + (((jj * 2 + (mi & 1)) ^ r7) << 4);

    asm volatile("bar.sync 1, %0;" :: "n"(kThreads) : "memory");

    int s = 0, ph = 0;
    auto release = [&]() {
        __syncwarp();
        if (lane == 0) mbar_arrive(empty + s * 8);
        if (++s == kNS) { s = 0; ph ^= 1; }
    };
    auto scale_acc = [&](float f) {
        const float fo = __shfl_xor_sync(0xffffffffu, f, 4);
        const float f0 = (g & 1) ? fo : f, f1 = (g & 1) ? f : fo;
#pragma unroll
        for (int j = 0; j < 8; j++) { acc[j][0] *= f0; acc[j][1] *= f1; acc[j][2] *= f0; acc[j][3] *= f1; }
    };
    auto qk = [&](float (&sv)[4]) {
        uint32_t a0 = ka0 + s * kSlotBytes, a1 = ka1 + s * kSlotBytes;
        asm volatile("" : "+r"(a0), "+r"(a1));
        mbar_wait(full + s * 8, ph);
        float sc[2][2][4];
#pragma unroll
        for (int u = 0; u < 2; u++)
#pragma unroll
            for (int c = 0; c < 2; c++) sc[u][c][0] = sc[u][c][1] = sc[u][c][2] = sc[u][c][3] = 0.f;
#pragma unroll
        for (int qd = 0; qd < 4; qd++) {
#pragma unroll
            for (int u = 0; u < 2; u++) {
                uint32_t r[4];
                ldsm4(r, ((qd & 1) ? a1 : a0) + u * 1024 + (qd >> 1) * kHalf);
                mma16816(sc[u][0], qa[2 * qd][0], 0u, qa[2 * qd][1], 0u, r[0], r[1]);
                mma16816(sc[u][1], qa[2 * qd + 1][0], 0u, qa[2 * qd + 1][1], 0u, r[2], r[3]);
            }
        }
        release();
        sv[0] = sc[0][0][0] + sc[0][1][0]; sv[1] = sc[0][0][1] + sc[0][1][1];
        sv[2] = sc[1][0][0] + sc[1][1][0]; sv[3] = sc[1][0][1] + sc[1][1][1];
        scale_scores(sv[0], sv[1]);
        scale_scores(sv[2], sv[3]);
        float mx = fmaxf(fmaxf(sv[0], sv[1]), fmaxf(sv[2], sv[3]));
        mx = fmaxf(mx, __shfl_xor_sync(0xffffffffu, mx, 1));
        mx = fmaxf(mx, __shfl_xor_sync(0xffffffffu, mx, 2));
        if (__any_sync(0xffffffffu, mx > m)) {
            const float mn = fmaxf(m, mx);
            const float f = ex2((m - mn) * kLog2e);
            m = mn; l *= f;
            scale_acc(f);
        }
    };
    auto probs = [&](const float (&sv)[4], float (&p)[4]) {
        const float ml = m * kLog2e;
#pragma unroll
        for (int x = 0; x < 4; x++) p[x] = ex2(fmaf(sv[x], kLog2e, -ml));
        l += (p[0] + p[1]) + (p[2] + p[3]);
    };
    auto pv = [&](uint32_t b0, uint32_t b1) {
        uint32_t a[4];
#pragma unroll
        for (int jj = 0; jj < 4; jj++) a[jj] = va[jj] + s * kSlotBytes;
        asm volatile("" : "+r"(a[0]), "+r"(a[1]), "+r"(a[2]), "+r"(a[3]));
        mbar_wait(full + s * 8, ph);
#pragma unroll
        for (int j = 0; j < 8; j++) {
            uint32_t r[4];
            ldsm4t(r, a[j & 3] + (j >> 2) * kHalf);
            mma16816(acc[j], r[0], r[1], r[2], r[3], b0, b1);
        }
    };

    float e0 = 0.f, e1 = 0.f;
    float scur[4], snxt[4], p[4];
    uint32_t bl0 = 0, bl1 = 0;
    qk(scur);
#pragma unroll 1
    for (int n = 0; n < kNT - 1; n++) {
        if (n == kOpenAt && !merger) st_rec(pp, 0ull, 0ull);
        qk(snxt);
        probs(scur, p);
        if (n == kNT - 2) {
            float p2[4];
            probs(snxt, p2);
            float lr = l + __shfl_xor_sync(0xffffffffu, l, 1);
            lr += __shfl_xor_sync(0xffffffffu, lr, 2);
            if (t == 0 && g < 2)
                asm volatile("st.shared.v2.f32 [%0], {%1,%2};" :: "r"(red + kNW * 1024 + warp * 16 + g * 8), "f"(m), "f"(lr) : "memory");
            asm volatile("bar.sync 2, %0;" :: "n"(kNC) : "memory");
            float mm[kNW][4];
            float M0 = -INFINITY, M1 = -INFINITY;
#pragma unroll
            for (int w = 0; w < kNW; w++) {
                asm volatile("ld.shared.v4.f32 {%0,%1,%2,%3}, [%4];"
                             : "=f"(mm[w][0]), "=f"(mm[w][1]), "=f"(mm[w][2]), "=f"(mm[w][3]) : "r"(red + kNW * 1024 + w * 16));
                M0 = fmaxf(M0, mm[w][0]); M1 = fmaxf(M1, mm[w][2]);
            }
            float L0 = 0.f, L1 = 0.f;
#pragma unroll
            for (int w = 0; w < kNW; w++) {
                L0 = fmaf(ex2((mm[w][0] - M0) * kLog2e), mm[w][1], L0);
                L1 = fmaf(ex2((mm[w][2] - M1) * kLog2e), mm[w][3], L1);
            }
            e0 = fmaf(M0, kLog2e, lg2(L0)); e1 = fmaf(M1, kLog2e, lg2(L1));
            const float f = ex2((m - ((g & 1) ? M1 : M0)) * kLog2e) * rcp((g & 1) ? L1 : L0);
            scale_acc(f);
#pragma unroll
            for (int x = 0; x < 4; x++) { p[x] *= f; p2[x] *= f; }
            bl0 = pack_bf16(p2[0], p2[1]); bl1 = pack_bf16(p2[2], p2[3]);
        }
        pv(pack_bf16(p[0], p[1]), pack_bf16(p[2], p[3]));
        release();
#pragma unroll
        for (int x = 0; x < 4; x++) scur[x] = snxt[x];
    }
    uint32_t sta = red + warp * 1024 + g * 16;
    uint32_t lda = red + (((tid >> 4) * 8 + (tid & 7)) * 16) + ((tid >> 3) & 1) * 8;
    asm volatile("" : "+r"(sta), "+r"(lda));

    uint64_t ra[kSplit - 1], rb[kSplit - 1];
    {
        uint32_t a[4];
#pragma unroll
        for (int jj = 0; jj < 4; jj++) a[jj] = va[jj] + s * kSlotBytes;
        asm volatile("" : "+r"(a[0]), "+r"(a[1]), "+r"(a[2]), "+r"(a[3]));
        mbar_wait(full + s * 8, ph);
#pragma unroll
        for (int x = 0; x < kSplit - 1; x++) { ra[x] = rb[x] = 0ull; ld_rec_if(ra[x], rb[x], pp + x * kD, merger); }
        uint32_t r[8][4];
#pragma unroll
        for (int j = 0; j < 8; j++) ldsm4t(r[j], a[j & 3] + (j >> 2) * kHalf);
#pragma unroll
        for (int j = 0; j < 8; j++) mma16816(acc[j], r[j][0], r[j][1], r[j][2], r[j][3], bl0, bl1);
    }
    if (t == 0) {
#pragma unroll
        for (int j = 0; j < 8; j++)
            asm volatile("st.shared.v4.f32 [%0], {%1,%2,%3,%4};"
                         :: "r"(sta + j * 128), "f"(acc[j][0]), "f"(acc[j][1]), "f"(acc[j][2]), "f"(acc[j][3]) : "memory");
    }
    asm volatile("bar.sync 2, %0;" :: "n"(kNC) : "memory");
    float av[kNW][2];
#pragma unroll
    for (int w = 0; w < kNW; w++)
        asm volatile("ld.shared.v2.f32 {%0,%1}, [%2];" : "=f"(av[w][0]), "=f"(av[w][1]) : "r"(lda + w * 1024));
    const float o0 = (av[0][0] + av[1][0]) + (av[2][0] + av[3][0]);
    const float o1 = (av[0][1] + av[1][1]) + (av[2][1] + av[3][1]);
    if (!merger) {
        st_rec(pp, rec_word(o0, e0), rec_word(o1, e1));
        return;
    }
#pragma unroll 1
    for (int it = 0;; it++) {
        bool miss[kSplit - 1];
#pragma unroll
        for (int x = 0; x < kSplit - 1; x++) miss[x] = (ra[x] >> 32) == 0 || (rb[x] >> 32) == 0;
        if (!(miss[0] || miss[1] || miss[2])) break;
        if (it > (1 << 22)) __trap();
#pragma unroll
        for (int x = 0; x < kSplit - 1; x++) ld_rec_if(ra[x], rb[x], pp + x * kD, miss[x]);
    }
    float E0 = e0, E1 = e1;
#pragma unroll
    for (int x = 0; x < kSplit - 1; x++) { E0 = fmaxf(E0, rec_lse(ra[x])); E1 = fmaxf(E1, rec_lse(rb[x])); }
    float w0 = ex2(e0 - E0), w1 = ex2(e1 - E1);
    float n0 = w0 * o0, n1 = w1 * o1;
#pragma unroll
    for (int x = 0; x < kSplit - 1; x++) {
        const float a = ex2(rec_lse(ra[x]) - E0), b = ex2(rec_lse(rb[x]) - E1);
        w0 += a; w1 += b;
        n0 = fmaf(a, rec_o(ra[x]), n0); n1 = fmaf(b, rec_o(rb[x]), n1);
    }
    op[0] = __float2bfloat16(n0 * rcp(w0));
    op[kD] = __float2bfloat16(n1 * rcp(w1));
#pragma unroll
    for (int x = 0; x < kSplit - 1; x++) st_rec(pp + x * kD, 0ull, 0ull);
}

typedef CUresult (*EncodeTiledFn)(CUtensorMap*, CUtensorMapDataType, cuuint32_t, void*, const cuuint64_t*, const cuuint64_t*,
                                  const cuuint32_t*, const cuuint32_t*, CUtensorMapInterleave, CUtensorMapSwizzle,
                                  CUtensorMapL2promotion, CUtensorMapFloatOOBfill);

CUtensorMap make_kv_map(EncodeTiledFn encode, void* base) {
    CUtensorMap m;
    const cuuint64_t dims[3] = {64, (cuuint64_t)kPairs * kC, 2};
    const cuuint64_t strides[2] = {256, 128};
    const cuuint32_t box[3] = {64, (cuuint32_t)kTile, 2};
    const cuuint32_t elem[3] = {1, 1, 1};
    encode(&m, CU_TENSOR_MAP_DATA_TYPE_BFLOAT16, 3, base, dims, strides, box, elem, CU_TENSOR_MAP_INTERLEAVE_NONE,
           CU_TENSOR_MAP_SWIZZLE_128B, CU_TENSOR_MAP_L2_PROMOTION_L2_256B, CU_TENSOR_MAP_FLOAT_OOB_FILL_NONE);
    return m;
}

}

extern "C" void kernel_launch(void* const* d_in, const int* in_sizes, int n_in, void* d_out, int out_size) {
    (void)in_sizes; (void)n_in; (void)out_size;
    static EncodeTiledFn encode = nullptr;
    static void* part = nullptr;
    static int pace_off_ns = 0, pace_tau_q8 = 0;
    if (!encode) {
        cudaDriverEntryPointQueryResult qr;
        cudaGetDriverEntryPoint("cuTensorMapEncodeTiled", (void**)&encode, cudaEnableDefault, &qr);
        cudaFuncSetAttribute(tree_attn_decode_kernel, cudaFuncAttributeMaxDynamicSharedMemorySize, kSmemBytes);
        cudaGetSymbolAddress(&part, g_part);
        int dev = 0, mem_khz = 0, bus_bits = 0;
        cudaGetDevice(&dev);
        cudaDeviceGetAttribute(&mem_khz, cudaDevAttrMemoryClockRate, dev);
        cudaDeviceGetAttribute(&bus_bits, cudaDevAttrGlobalMemoryBusWidth, dev);
        const double bytes_per_ns = 2.0 * mem_khz * 1e-6 * bus_bits / 8.0;
        if (bytes_per_ns > 0.0) {
            const double tau = (double)kPairs * kSplit * kSlotBytes / (0.9595 * bytes_per_ns);
            pace_tau_q8 = (int)(tau * 256.0);
            pace_off_ns = (int)(2.1 * tau);
        }
    }
    const CUtensorMap tmK = make_kv_map(encode, d_in[1]);
    const CUtensorMap tmV = make_kv_map(encode, d_in[2]);
    tree_attn_decode_kernel<<<kPairs * kSplit, kThreads, kSmemBytes>>>(
        tmK, tmV, (const __nv_bfloat16*)d_in[0], (const __nv_bfloat16*)d_in[3], (const __nv_bfloat16*)d_in[4],
        (const __nv_bfloat16*)d_in[5], (__nv_bfloat16*)d_out, (uint4*)part,
        (const __nv_bfloat16*)d_in[1], (const __nv_bfloat16*)d_in[2], pace_off_ns, pace_tau_q8);
}
```

```cpp
#include <cuda_runtime.h>
#include <cuda_bf16.h>
#include <cuda.h>
#include <stdint.h>

namespace {

constexpr int kB = 2, kHkv = 16, kC = 8192, kD = 128;
constexpr int kPairs = kB * kHkv;
constexpr int kSplit = 4;
constexpr int kKeysPerCta = kC / kSplit;
constexpr int kTile = 64;
constexpr int kNW = kTile / 16;
constexpr int kNC = kNW * 32;
constexpr int kThreads = kNC + 32;
constexpr int kNS = 8;
constexpr int kNT = kKeysPerCta / kTile;
constexpr int kNL = 2 * kNT;
constexpr int kLead = 4;
constexpr int kSlotBytes = kTile * kD * 2;
constexpr uint32_t kHalf = kTile * 128;
constexpr int kFreeLoads = 4;
constexpr int kMinInflight = 2;
constexpr int kMergerLagNs = 250;
constexpr float kScale = 0.08838834764831845f;
constexpr float kLog2e = 1.4426950408889634f;
constexpr uint32_t kOffAcc = 0;
constexpr uint32_t kOffMl = kOffAcc + kNW * 1024;
constexpr uint32_t kOffStat = kOffMl + kNW * 16;
constexpr uint32_t kOffWgt = kOffStat + 16;
constexpr uint32_t kOffSc = kOffWgt + 32;
constexpr uint32_t kOffBar = kOffSc + (kLead + 1) * kNW * 256;
constexpr int kSmemBytes = 1024   + kNS * kSlotBytes + kOffBar + 2 * kNS * 8;
static_assert(kNC == kD && kSplit == 4 && kNW == 4, "layout assumptions");
static_assert(kLead >= 2 && kLead + 1 <= kNS, "load order assumptions");

constexpr int kBoxWords = kD + 16;
__device__ __align__(128) uint64_t g_mailbox[kPairs * kSplit * kBoxWords];

__device__ __forceinline__ uint32_t smem_u32(const void* p) { return (uint32_t)__cvta_generic_to_shared(p); }
__device__ __forceinline__ uint32_t timer_ns() { uint32_t t; asm volatile("mov.u32 %0, %globaltimer_lo;" : "=r"(t)); return t; }
__device__ __forceinline__ void mbar_init(uint32_t bar, uint32_t cnt) {
    asm volatile("mbarrier.init.shared::cta.b64 [%0], %1;" :: "r"(bar), "r"(cnt) : "memory");
}
__device__ __forceinline__ void mbar_expect_tx(uint32_t bar, uint32_t bytes) {
    asm volatile("mbarrier.arrive.expect_tx.shared::cta.b64 _, [%0], %1;" :: "r"(bar), "r"(bytes) : "memory");
}
__device__ __forceinline__ void mbar_arrive(uint32_t bar) {
    asm volatile("mbarrier.arrive.shared::cta.b64 _, [%0];" :: "r"(bar) : "memory");
}
__device__ __forceinline__ bool mbar_test(uint32_t bar, uint32_t parity) {
    uint32_t ok;
    asm volatile("{\n.reg .pred p;\nmbarrier.test_wait.parity.shared::cta.b64 p, [%1], %2;\nselp.u32 %0, 1, 0, p;\n}"
                 : "=r"(ok) : "r"(bar), "r"(parity) : "memory");
    return ok != 0;
}
__device__ __forceinline__ void mbar_wait(uint32_t bar, uint32_t parity) {
    asm volatile(
        "{\n"
        ".reg .pred p, q;\n"
        ".reg .u32 c;\n"
        "mov.u32 c, 0;\n"
        "LAB_WAIT:\n"
        "mbarrier.try_wait.parity.shared::cta.b64 p, [%0], %1;\n"
        "@p bra LAB_DONE;\n"
        "add.u32 c, c, 1;\n"
        "setp.lt.u32 q, c, 0x1000000;\n"
        "@q bra LAB_WAIT;\n"
        "trap;\n"
        "LAB_DONE:\n"
        "}\n" :: "r"(bar), "r"(parity) : "memory");
}
template <int ID, int N> __device__ __forceinline__ void bar_sync() { asm volatile("bar.sync %0, %1;" :: "n"(ID), "n"(N) : "memory"); }
template <int ID, int N> __device__ __forceinline__ void bar_arrive() { asm volatile("bar.arrive %0, %1;" :: "n"(ID), "n"(N) : "memory"); }
__device__ __forceinline__ void tma_tile(uint32_t dst, const CUtensorMap* tm, int row, uint32_t bar) {
    asm volatile("cp.async.bulk.tensor.3d.shared::cluster.global.mbarrier::complete_tx::bytes [%0], [%1, {%3, %4, %3}], [%2];"
                 :: "r"(dst), "l"(tm), "r"(bar), "r"(0), "r"(row) : "memory");
}
__device__ __forceinline__ void ldsm4(uint32_t (&r)[4], uint32_t addr) {
    asm volatile("ldmatrix.sync.aligned.m8n8.x4.shared.b16 {%0,%1,%2,%3}, [%4];"
                 : "=r"(r[0]), "=r"(r[1]), "=r"(r[2]), "=r"(r[3]) : "r"(addr));
}
__device__ __forceinline__ void ldsm4t(uint32_t (&r)[4], uint32_t addr) {
    asm volatile("ldmatrix.sync.aligned.m8n8.x4.trans.shared.b16 {%0,%1,%2,%3}, [%4];"
                 : "=r"(r[0]), "=r"(r[1]), "=r"(r[2]), "=r"(r[3]) : "r"(addr));
}
__device__ __forceinline__ void mma16816(float (&d)[4], uint32_t a0, uint32_t a1, uint32_t a2, uint32_t a3, uint32_t b0, uint32_t b1) {
    asm volatile("mma.sync.aligned.m16n8k16.row.col.f32.bf16.bf16.f32 {%0,%1,%2,%3}, {%4,%5,%6,%7}, {%8,%9}, {%0,%1,%2,%3};"
                 : "+f"(d[0]), "+f"(d[1]), "+f"(d[2]), "+f"(d[3]) : "r"(a0), "r"(a1), "r"(a2), "r"(a3), "r"(b0), "r"(b1));
}
__device__ __forceinline__ void sts2(uint32_t a, float x, float y) { asm volatile("st.shared.v2.f32 [%0], {%1,%2};" :: "r"(a), "f"(x), "f"(y) : "memory"); }
__device__ __forceinline__ void sts4(uint32_t a, float x, float y, float z, float w) {
    asm volatile("st.shared.v4.f32 [%0], {%1,%2,%3,%4};" :: "r"(a), "f"(x), "f"(y), "f"(z), "f"(w) : "memory");
}
__device__ __forceinline__ void lds4(float (&v)[4], uint32_t a) {
    asm volatile("ld.shared.v4.f32 {%0,%1,%2,%3}, [%4];" : "=f"(v[0]), "=f"(v[1]), "=f"(v[2]), "=f"(v[3]) : "r"(a) : "memory");
}
__device__ __forceinline__ float ex2(float x) { float y; asm("ex2.approx.ftz.f32 %0, %1;" : "=f"(y) : "f"(x)); return y; }
__device__ __forceinline__ float rcp(float x) { float y; asm("rcp.approx.ftz.f32 %0, %1;" : "=f"(y) : "f"(x)); return y; }
__device__ __forceinline__ float expdiff(float a, float b) { return ex2((a - b) * kLog2e); }
__device__ __forceinline__ float sel(uint32_t c, float a, float b) {
    float r; asm("{\n.reg .pred p;\nsetp.ne.u32 p, %3, 0;\nselp.f32 %0, %1, %2, p;\n}" : "=f"(r) : "f"(a), "f"(b), "r"(c)); return r;
}
__device__ __forceinline__ uint32_t pack_bf16(float lo, float hi) {
    uint32_t r; asm("cvt.rn.bf16x2.f32 %0, %1, %2;" : "=r"(r) : "f"(hi), "f"(lo)); return r;
}
__device__ __forceinline__ float bf_lo(uint32_t v) { return __uint_as_float(v << 16); }
__device__ __forceinline__ float bf_hi(uint32_t v) { return __uint_as_float(v & 0xffff0000u); }
__device__ __forceinline__ float bf_round(float x) { return __bfloat162float(__float2bfloat16(x)); }
__device__ __forceinline__ uint32_t scale_scores(float a, float b) {
    const uint32_t r = pack_bf16(a, b);
    return pack_bf16(bf_lo(r) * kScale, bf_hi(r) * kScale);
}
__device__ __forceinline__ void st_bf16(__nv_bfloat16* p, float v) {
    asm volatile("{\n.reg .b16 h;\ncvt.rn.bf16.f32 h, %1;\nst.global.b16 [%0], h;\n}" :: "l"(p), "f"(v) : "memory");
}
__device__ __forceinline__ void st_word(uint64_t* p, uint64_t v) {
    asm volatile("st.relaxed.gpu.global.b64 [%0], %1;" :: "l"(p), "l"(v) : "memory");
}
__device__ __forceinline__ void ld_word_if(uint64_t& a, const uint64_t* p, bool pred) {
    asm volatile("{\n.reg .pred p;\nsetp.ne.u32 p, %2, 0;\n@p ld.relaxed.gpu.global.b64 %0, [%1];\n}"
                 : "+l"(a) : "l"(p), "r"((uint32_t)pred) : "memory");
}
__device__ __forceinline__ void ld_word2_if(uint64_t& a, uint64_t& b, const uint64_t* p, bool pred) {
    asm volatile("{\n.reg .pred p;\nsetp.ne.u32 p, %3, 0;\n@p ld.relaxed.gpu.global.v2.b64 {%0, %1}, [%2];\n}"
                 : "+l"(a), "+l"(b) : "l"(p), "r"((uint32_t)pred) : "memory");
}
__device__ __forceinline__ uint64_t make_word(float lo, float hi) {
    uint32_t u = __float_as_uint(lo);
    if (u == 0u) u = 0x80000000u;
    return ((uint64_t)__float_as_uint(hi) << 32) | u;
}
__device__ __forceinline__ float word_lo(uint64_t w) { return __uint_as_float((uint32_t)w); }
__device__ __forceinline__ float word_hi(uint64_t w) { return __uint_as_float((uint32_t)(w >> 32)); }
__device__ __forceinline__ bool missing(uint64_t w) { return (uint32_t)w == 0u; }

__global__ void __launch_bounds__(kThreads, 1)
tree_attn_decode_kernel(const __grid_constant__ CUtensorMap tmK, const __grid_constant__ CUtensorMap tmV,
                        const __nv_bfloat16* __restrict__ q, const __nv_bfloat16* __restrict__ k_cache,
                        const __nv_bfloat16* __restrict__ k_tree, const __nv_bfloat16* __restrict__ v_tree,
                        const __nv_bfloat16* __restrict__ mask, __nv_bfloat16* __restrict__ out,
                        uint64_t* __restrict__ mailbox, int pace_off_ns, int pace_tau_q8)
{
    const int row0 = blockIdx.x * kKeysPerCta;
    if (threadIdx.x == 0)
        asm volatile("cp.async.bulk.prefetch.L2.global [%0], %1;" :: "l"(k_cache + (size_t)row0 * kD), "n"(3 * kSlotBytes) : "memory");

    extern __shared__ uint8_t smem_raw[];
    const uint32_t sbase = (smem_u32(smem_raw) + 1023) & ~1023u;
    const uint32_t aux = sbase + kNS * kSlotBytes;
    const uint32_t full = aux + kOffBar, empty = full + kNS * 8;

    uint32_t t0 = 0;
    if (threadIdx.x == kNC) {
        t0 = timer_ns();
#pragma unroll
        for (int s = 0; s < kNS; s++) mbar_init(full + s * 8, 1);
        asm volatile("fence.mbarrier_init.release.cluster;" ::: "memory");
#pragma unroll
        for (int i = 0; i < 3; i++) {
            mbar_expect_tx(full + i * 8, kSlotBytes);
            tma_tile(sbase + i * kSlotBytes, &tmK, row0 + i * kTile, full + i * 8);
        }
#pragma unroll
        for (int s = 0; s < kNS; s++) mbar_init(empty + s * 8, kNW);
    }
    const int warp = threadIdx.x >> 5, lane = threadIdx.x & 31;
    const int pair = blockIdx.x >> 2;
    const bool merger = (blockIdx.x & 3) == kSplit - 1;

    if (warp == kNW) {
        __syncwarp();
        bar_arrive<1, kThreads>();
        uint64_t* stat = mailbox + (size_t)pair * kSplit * kBoxWords + kD;
        asm volatile("" : "+l"(stat));
        uint64_t wm[3] = {0ull, 0ull, 0ull}, wl[3] = {0ull, 0ull, 0ull};
        if (lane == 0) {
            const int off = pace_off_ns + (merger ? kMergerLagNs : 0);
#pragma unroll 1
            for (int i = 3; i < kNL; i++) {
                const int s = i % kNS;
                mbar_wait(empty + s * 8, ((i / kNS) & 1) ^ 1);
                if (i >= kFreeLoads) {
                    const uint32_t due = (uint32_t)(off + (((i - kFreeLoads) * pace_tau_q8) >> 8));
                    const int j = i - kMinInflight;
                    while (timer_ns() - t0 < due && !mbar_test(full + (j % kNS) * 8, (j / kNS) & 1)) { }
                }
                if (i == kNL - 1) {
#pragma unroll
                    for (int y = 0; y < 3; y++) ld_word2_if(wm[y], wl[y], stat + y * kBoxWords, merger);
                }
                const int j = i - kLead;
                const bool is_k = i < kLead || (i < kNL - kLead && !(j & 1));
                const int tile = i < kLead ? i : i >= kNL - kLead ? i - kNT : is_k ? kLead + (j >> 1) : (j >> 1);
                mbar_expect_tx(full + s * 8, kSlotBytes);
                tma_tile(sbase + s * kSlotBytes, is_k ? &tmK : &tmV, row0 + tile * kTile, full + s * 8);
            }
        }
        if (!merger) return;
        if (lane == 0) {
#pragma unroll 1
            for (int it = 0;; it++) {
                bool miss[3];
#pragma unroll
                for (int y = 0; y < 3; y++) miss[y] = missing(wm[y]) || missing(wl[y]);
                if (!(miss[0] || miss[1] || miss[2])) break;
                if (it > (1 << 22)) __trap();
#pragma unroll
                for (int y = 0; y < 3; y++) ld_word2_if(wm[y], wl[y], stat + y * kBoxWords, miss[y]);
            }
        }
        __syncwarp();
        if (lane < 12) st_word(stat + (lane >> 2) * kBoxWords + (lane & 3), 0ull);
        bar_sync<3, 64>();
        if (lane == 0) {
            float own[4], c0[4], c1[4];
            lds4(own, aux + kOffStat);
            const float M0 = fmaxf(fmaxf(own[0], word_lo(wm[0])), fmaxf(word_lo(wm[1]), word_lo(wm[2])));
            const float M1 = fmaxf(fmaxf(own[1], word_hi(wm[0])), fmaxf(word_hi(wm[1]), word_hi(wm[2])));
#pragma unroll
            for (int y = 0; y < 3; y++) {
                c0[y] = expdiff(word_lo(wm[y]), M0) * word_lo(wl[y]);
                c1[y] = expdiff(word_hi(wm[y]), M1) * word_hi(wl[y]);
            }
            c0[3] = expdiff(own[0], M0) * own[2];
            c1[3] = expdiff(own[1], M1) * own[3];
            const float r0 = rcp((c0[0] + c0[1]) + (c0[2] + c0[3])), r1 = rcp((c1[0] + c1[1]) + (c1[2] + c1[3]));
            sts4(aux + kOffWgt, c0[0] * r0, c0[1] * r0, c0[2] * r0, c0[3] * r0);
            sts4(aux + kOffWgt + 16, c1[0] * r1, c1[1] * r1, c1[2] * r1, c1[3] * r1);
        }
        __syncwarp();
        bar_arrive<4, kThreads>();
        return;
    }

    const int g = lane >> 2, t = lane & 3;

    uint32_t qa[8][2];
    {
        const uint32_t* qp = reinterpret_cast<const uint32_t*>(q + (size_t)(pair * 2 + (g & 1)) * kD);
#pragma unroll
        for (int j = 0; j < 8; j++) { qa[j][0] = __ldg(qp + j * 8 + t); qa[j][1] = __ldg(qp + j * 8 + 4 + t); }
    }
    const int mydim = warp * 32 + (t >> 1) * 16 + (t & 1) * 8 + g;
    uint64_t* box = mailbox + (size_t)(merger ? pair * kSplit : blockIdx.x) * kBoxWords;
    uint64_t* slot = box + mydim;
    __nv_bfloat16* op = out + (size_t)pair * 2 * kD + mydim;
    asm volatile("" : "+l"(box), "+l"(slot), "+l"(op));

    float acc[8][4];
    float m = -INFINITY, l = 0.f;
#pragma unroll
    for (int j = 0; j < 8; j++) { acc[j][0] = acc[j][1] = acc[j][2] = acc[j][3] = 0.f; }
    if (merger && warp == 0) {
        const uint32_t* kp = reinterpret_cast<const uint32_t*>(k_tree + (size_t)pair * kD);
        const __nv_bfloat16* vp = v_tree + (size_t)pair * kD;
        float s4[4] = {0.f, 0.f, 0.f, 0.f};
#pragma unroll
        for (int j = 0; j < 8; j++) {
            mma16816(s4, qa[j][0], 0u, qa[j][1], 0u, __ldg(kp + j * 8 + t), __ldg(kp + j * 8 + 4 + t));
            acc[j][0] = acc[j][1] = __bfloat162float(vp[j * 16 + g]);
            acc[j][2] = acc[j][3] = __bfloat162float(vp[j * 16 + 8 + g]);
        }
        const float keep = __bfloat162float(mask[pair / kHkv]);
        m = bf_round(bf_lo(scale_scores(s4[0], s4[1])) + bf_round(bf_round(1.0f - keep) * -1000000000.0f));
        l = (t == 0) ? 1.f : 0.f;
    }

    const int r7 = lane & 7, mi = lane >> 3;
    const uint32_t ka0 = sbase + (uint32_t)(warp * 16 + r7) * 128 + ((mi ^ r7) << 4);
    const uint32_t ka1 = sbase + (uint32_t)(warp * 16 + r7) * 128 + (((4 + mi) ^ r7) << 4);
    uint32_t va[4];
#pragma unroll
    for (int jj = 0; jj < 4; jj++)
        va[jj] = sbase + (uint32_t)(warp * 16 + (mi >> 1) * 8 + r7) * 128 + (((jj * 2 + (mi & 1)) ^ r7) << 4);

    bar_sync<1, kThreads>();

    int s = 0, ph = 0;
    auto release = [&]() {
        __syncwarp();
        if (lane == 0) mbar_arrive(empty + s * 8);
        if (++s == kNS) { s = 0; ph ^= 1; }
    };
    auto probs = [&](uint32_t s01, uint32_t s23, float (&p)[4]) {
        p[0] = expdiff(bf_lo(s01), m); p[1] = expdiff(bf_hi(s01), m);
        p[2] = expdiff(bf_lo(s23), m); p[3] = expdiff(bf_hi(s23), m);
        l += (p[0] + p[1]) + (p[2] + p[3]);
    };

    uint32_t fifo[kLead + 1][2];
#pragma unroll
    for (int x = 0; x <= kLead; x++) fifo[x][0] = fifo[x][1] = 0u;
#pragma unroll 1
    for (int n = -kLead;; n++) {
#pragma unroll
        for (int x = 0; x < kLead; x++) { fifo[x][0] = fifo[x + 1][0]; fifo[x][1] = fifo[x + 1][1]; }
        {
            uint32_t a0 = ka0 + s * kSlotBytes, a1 = ka1 + s * kSlotBytes;
            asm volatile("" : "+r"(a0), "+r"(a1));
            mbar_wait(full + s * 8, ph);
            float sc[2][2][4];
#pragma unroll
            for (int u = 0; u < 2; u++)
#pragma unroll
                for (int c = 0; c < 2; c++) sc[u][c][0] = sc[u][c][1] = sc[u][c][2] = sc[u][c][3] = 0.f;
#pragma unroll
            for (int qd = 0; qd < 4; qd++) {
#pragma unroll
                for (int u = 0; u < 2; u++) {
                    uint32_t r[4];
                    ldsm4(r, ((qd & 1) ? a1 : a0) + u * 1024 + (qd >> 1) * kHalf);
                    mma16816(sc[u][0], qa[2 * qd][0], 0u, qa[2 * qd][1], 0u, r[0], r[1]);
                    mma16816(sc[u][1], qa[2 * qd + 1][0], 0u, qa[2 * qd + 1][1], 0u, r[2], r[3]);
                }
            }
            release();
            const uint32_t s01 = scale_scores(sc[0][0][0] + sc[0][1][0], sc[0][0][1] + sc[0][1][1]);
            const uint32_t s23 = scale_scores(sc[1][0][0] + sc[1][1][0], sc[1][0][1] + sc[1][1][1]);
            fifo[kLead][0] = s01; fifo[kLead][1] = s23;
            float mx = fmaxf(fmaxf(bf_lo(s01), bf_hi(s01)), fmaxf(bf_lo(s23), bf_hi(s23)));
            mx = fmaxf(mx, __shfl_xor_sync(0xffffffffu, mx, 1));
            mx = fmaxf(mx, __shfl_xor_sync(0xffffffffu, mx, 2));
            if (__any_sync(0xffffffffu, mx > m)) {
                const float mn = fmaxf(m, mx);
                const float f = expdiff(m, mn), fo = __shfl_xor_sync(0xffffffffu, f, 4);
                const float f0 = (g & 1) ? fo : f, f1 = (g & 1) ? f : fo;
                m = mn; l *= f;
#pragma unroll
                for (int j = 0; j < 8; j++) { acc[j][0] *= f0; acc[j][1] *= f1; acc[j][2] *= f0; acc[j][3] *= f1; }
            }
        }
        if (n == kNT - kLead - 1) break;
        if (n >= 0) {
            float p[4];
            probs(fifo[0][0], fifo[0][1], p);
            const uint32_t b0 = pack_bf16(p[0], p[1]), b1 = pack_bf16(p[2], p[3]);
            uint32_t a[4];
#pragma unroll
            for (int jj = 0; jj < 4; jj++) a[jj] = va[jj] + s * kSlotBytes;
            asm volatile("" : "+r"(a[0]), "+r"(a[1]), "+r"(a[2]), "+r"(a[3]));
            mbar_wait(full + s * 8, ph);
#pragma unroll
            for (int j = 0; j < 8; j++) {
                uint32_t r[4];
                ldsm4t(r, a[j & 3] + (j >> 2) * kHalf);
                mma16816(acc[j], r[0], r[1], r[2], r[3], b0, b1);
            }
            release();
        }
    }

    float c[2][4];
    uint32_t pb[kLead + 1][kNW][2];
    {
#pragma unroll
        for (int x = 0; x <= kLead; x++) {
            float p[4];
            probs(fifo[x][0], fifo[x][1], p);
            asm volatile("st.shared.v2.b32 [%0], {%1,%2};"
                         :: "r"(aux + kOffSc + (x * kNW + warp) * 256 + lane * 8), "r"(fifo[x][0]), "r"(fifo[x][1]) : "memory");
        }
        float lr = l + __shfl_xor_sync(0xffffffffu, l, 1);
        lr += __shfl_xor_sync(0xffffffffu, lr, 2);
        if (t == 0) {
#pragma unroll
            for (int j = 0; j < 8; j++) sts4(aux + kOffAcc + warp * 1024 + j * 128 + g * 16, acc[j][0], acc[j][1], acc[j][2], acc[j][3]);
            if (g < 2) sts2(aux + kOffMl + warp * 16 + g * 8, m, lr);
        }
        bar_sync<2, kNC>();
        float mm[kNW][4];
        float M0 = -INFINITY, M1 = -INFINITY;
#pragma unroll
        for (int w = 0; w < kNW; w++) {
            lds4(mm[w], aux + kOffMl + w * 16);
            M0 = fmaxf(M0, mm[w][0]); M1 = fmaxf(M1, mm[w][2]);
        }
        float f0[kNW], f1[kNW], L0 = 0.f, L1 = 0.f;
#pragma unroll
        for (int w = 0; w < kNW; w++) {
            f0[w] = expdiff(mm[w][0], M0); f1[w] = expdiff(mm[w][2], M1);
            L0 = fmaf(f0[w], mm[w][1], L0); L1 = fmaf(f1[w], mm[w][3], L1);
        }
        if (warp == 0) {
            if (!merger) {
                if (lane < 4) st_word(box + kD + lane, (lane & 1) ? make_word(L0, L1) : make_word(M0, M1));
            } else {
                if (lane == 0) sts4(aux + kOffStat, M0, M1, L0, L1);
                __syncwarp();
                bar_arrive<3, 64>();
            }
        }
        const float r0 = rcp(L0), r1 = rcp(L1);
#pragma unroll
        for (int jj = 0; jj < 2; jj++) {
            c[jj][0] = c[jj][1] = c[jj][2] = c[jj][3] = 0.f;
#pragma unroll
            for (int w = 0; w < kNW; w++) {
                float v[4];
                lds4(v, aux + kOffAcc + w * 1024 + (warp * 2 + jj) * 128 + g * 16);
                c[jj][0] = fmaf(f0[w], v[0], c[jj][0]); c[jj][1] = fmaf(f1[w], v[1], c[jj][1]);
                c[jj][2] = fmaf(f0[w], v[2], c[jj][2]); c[jj][3] = fmaf(f1[w], v[3], c[jj][3]);
            }
            c[jj][0] *= r0; c[jj][1] *= r1; c[jj][2] *= r0; c[jj][3] *= r1;
        }
        const float Mh = (g & 1) ? M1 : M0, rh = (g & 1) ? r1 : r0;
#pragma unroll
        for (int x = 0; x <= kLead; x++)
#pragma unroll
            for (int w = 0; w < kNW; w++) {
                uint32_t s01, s23;
                asm volatile("ld.shared.v2.b32 {%0,%1}, [%2];"
                             : "=r"(s01), "=r"(s23) : "r"(aux + kOffSc + (x * kNW + w) * 256 + lane * 8) : "memory");
                pb[x][w][0] = pack_bf16(expdiff(bf_lo(s01), Mh) * rh, expdiff(bf_hi(s01), Mh) * rh);
                pb[x][w][1] = pack_bf16(expdiff(bf_lo(s23), Mh) * rh, expdiff(bf_hi(s23), Mh) * rh);
            }
    }

    uint32_t la[2];
#pragma unroll
    for (int jj = 0; jj < 2; jj++)
        la[jj] = sbase + (warp >> 1) * kHalf + (uint32_t)((mi >> 1) * 8 + r7) * 128 + ((((warp & 1) * 4 + jj * 2 + (mi & 1)) ^ r7) << 4);
    uint64_t ow[3] = {0ull, 0ull, 0ull};
    asm volatile("" : "+r"(la[0]), "+r"(la[1]), "+l"(ow[0]), "+l"(ow[1]), "+l"(ow[2]));
    float w0[4], w1[4];
    float cb[2][4] = {{0.f, 0.f, 0.f, 0.f}, {0.f, 0.f, 0.f, 0.f}};
#pragma unroll
    for (int x = 0; x <= kLead; x++) {
        constexpr int kFirst = kNL - 1 - kLead;
        const int sl = (kFirst + x) % kNS;
        if (x == 1 && !merger) st_word(slot, 0ull);
        if (x == kLead && merger) {
            bar_sync<4, kThreads>();
            lds4(w0, aux + kOffWgt);
            lds4(w1, aux + kOffWgt + 16);
        }
        mbar_wait(full + sl * 8, ((kFirst + x) / kNS) & 1);
        if (x == kLead) {
#pragma unroll
            for (int y = 0; y < 3; y++) ld_word_if(ow[y], slot + y * kBoxWords, merger);
        }
        uint32_t r[kNW][2][4];
#pragma unroll
        for (int k = 0; k < kNW; k++)
#pragma unroll
            for (int jj = 0; jj < 2; jj++) ldsm4t(r[k][jj], la[jj] + sl * kSlotBytes + k * 2048);
#pragma unroll
        for (int k = 0; k < kNW; k++)
#pragma unroll
            for (int jj = 0; jj < 2; jj++)
                mma16816((k & 1) ? cb[jj] : c[jj], r[k][jj][0], r[k][jj][1], r[k][jj][2], r[k][jj][3], pb[x][k][0], pb[x][k][1]);
    }
    const uint32_t t1 = t & 1, t2 = t & 2;
    const float o0 = sel(t2, sel(t1, c[1][2], c[1][0]), sel(t1, c[0][2], c[0][0])) + sel(t2, sel(t1, cb[1][2], cb[1][0]), sel(t1, cb[0][2], cb[0][0]));
    const float o1 = sel(t2, sel(t1, c[1][3], c[1][1]), sel(t1, c[0][3], c[0][1])) + sel(t2, sel(t1, cb[1][3], cb[1][1]), sel(t1, cb[0][3], cb[0][1]));
    if (!merger) {
        st_word(slot, make_word(o0, o1));
        return;
    }
    const float a0 = w0[3] * o0, a1 = w1[3] * o1;
#pragma unroll 1
    for (int it = 0; missing(ow[0]) || missing(ow[1]) || missing(ow[2]); it++) {
        if (it > (1 << 22)) __trap();
#pragma unroll
        for (int y = 0; y < 3; y++) ld_word_if(ow[y], slot + y * kBoxWords, missing(ow[y]));
    }
    st_bf16(op, fmaf(w0[0], word_lo(ow[0]), a0) + fmaf(w0[1], word_lo(ow[1]), w0[2] * word_lo(ow[2])));
    st_bf16(op + kD, fmaf(w1[0], word_hi(ow[0]), a1) + fmaf(w1[1], word_hi(ow[1]), w1[2] * word_hi(ow[2])));
#pragma unroll
    for (int y = 0; y < 3; y++) st_word(slot + y * kBoxWords, 0ull);
}

typedef CUresult (*EncodeTiledFn)(CUtensorMap*, CUtensorMapDataType, cuuint32_t, void*, const cuuint64_t*, const cuuint64_t*,
                                  const cuuint32_t*, const cuuint32_t*, CUtensorMapInterleave, CUtensorMapSwizzle,
                                  CUtensorMapL2promotion, CUtensorMapFloatOOBfill);

CUtensorMap make_kv_map(EncodeTiledFn encode, void* base) {
    CUtensorMap m;
    const cuuint64_t dims[3] = {64, (cuuint64_t)kPairs * kC, 2};
    const cuuint64_t strides[2] = {256, 128};
    const cuuint32_t box[3] = {64, (cuuint32_t)kTile, 2};
    const cuuint32_t elem[3] = {1, 1, 1};
    encode(&m, CU_TENSOR_MAP_DATA_TYPE_BFLOAT16, 3, base, dims, strides, box, elem, CU_TENSOR_MAP_INTERLEAVE_NONE,
           CU_TENSOR_MAP_SWIZZLE_128B, CU_TENSOR_MAP_L2_PROMOTION_L2_256B, CU_TENSOR_MAP_FLOAT_OOB_FILL_NONE);
    return m;
}

}

extern "C" void kernel_launch(void* const* d_in, const int* in_sizes, int n_in, void* d_out, int out_size) {
    (void)in_sizes; (void)n_in; (void)out_size;
    static EncodeTiledFn encode = nullptr;
    static void* mailbox = nullptr;
    static int pace_off_ns = 0, pace_tau_q8 = 0;
    if (!encode) {
        cudaDriverEntryPointQueryResult qr;
        cudaGetDriverEntryPoint("cuTensorMapEncodeTiled", (void**)&encode, cudaEnableDefault, &qr);
        cudaFuncSetAttribute(tree_attn_decode_kernel, cudaFuncAttributeMaxDynamicSharedMemorySize, kSmemBytes);
        cudaGetSymbolAddress(&mailbox, g_mailbox);
        int dev = 0, mem_khz = 0, bus_bits = 0;
        cudaGetDevice(&dev);
        cudaDeviceGetAttribute(&mem_khz, cudaDevAttrMemoryClockRate, dev);
        cudaDeviceGetAttribute(&bus_bits, cudaDevAttrGlobalMemoryBusWidth, dev);
        const double bytes_per_ns = 2.0 * mem_khz * 1e-6 * bus_bits / 8.0;
        if (bytes_per_ns > 0.0) {
            const double tau = (double)kPairs * kSplit * kSlotBytes / (0.9595 * bytes_per_ns);
            pace_tau_q8 = (int)(tau * 256.0);
            pace_off_ns = (int)(2.1 * tau);
        }
    }
    const CUtensorMap tmK = make_kv_map(encode, d_in[1]);
    const CUtensorMap tmV = make_kv_map(encode, d_in[2]);
    tree_attn_decode_kernel<<<kPairs * kSplit, kThreads, kSmemBytes>>>(
        tmK, tmV, (const __nv_bfloat16*)d_in[0], (const __nv_bfloat16*)d_in[1], (const __nv_bfloat16*)d_in[3],
        (const __nv_bfloat16*)d_in[4], (const __nv_bfloat16*)d_in[5], (__nv_bfloat16*)d_out, (uint64_t*)mailbox,
        pace_off_ns, pace_tau_q8);
}
```

```cpp
#include <cuda_runtime.h>
#include <cuda_bf16.h>
#include <cuda.h>
#include <stdint.h>

namespace {

constexpr int kB = 2, kHkv = 16, kC = 8192, kD = 128;
constexpr int kPairs = kB * kHkv;
constexpr int kSplit = 4;
constexpr int kKeysPerCta = kC / kSplit;
constexpr int kTile = 64;
constexpr int kNW = kTile / 16;
constexpr int kNC = kNW * 32;
constexpr int kThreads = kNC + 32;
constexpr int kNS = 10;
constexpr int kNT = kKeysPerCta / kTile;
constexpr int kNL = 2 * kNT;
constexpr int kLead = 6;
constexpr int kSlotBytes = kTile * kD * 2;
constexpr uint32_t kHalf = kTile * 128;
constexpr int kFreeLoads = 4;
constexpr int kMinInflight = 2;
constexpr int kMergerLagNs = 250;
constexpr float kScale = 0.08838834764831845f;
constexpr float kLog2e = 1.4426950408889634f;
constexpr uint32_t kOffAcc = 0;
constexpr uint32_t kOffMl = kOffAcc + kNW * 1024;
constexpr uint32_t kOffStat = kOffMl + kNW * 16;
constexpr uint32_t kOffWgt = kOffStat + 16;
constexpr uint32_t kOffSc = kOffWgt + 32;
constexpr uint32_t kOffBar = kOffSc + (kLead + 1) * kNW * 256;
constexpr int kSmemBytes = 1024   + kNS * kSlotBytes + kOffBar + 2 * kNS * 8;
static_assert(kNC == kD && kSplit == 4 && kNW == 4, "layout assumptions");
static_assert(kLead >= 3 && kLead + 1 <= kNS, "load order assumptions");

constexpr int kBoxWords = kD + 16;
__device__ __align__(128) uint64_t g_mailbox[kPairs * kSplit * kBoxWords];

__device__ __forceinline__ uint32_t smem_u32(const void* p) { return (uint32_t)__cvta_generic_to_shared(p); }
__device__ __forceinline__ uint32_t timer_ns() { uint32_t t; asm volatile("mov.u32 %0, %globaltimer_lo;" : "=r"(t)); return t; }
__device__ __forceinline__ void mbar_init(uint32_t bar, uint32_t cnt) {
    asm volatile("mbarrier.init.shared::cta.b64 [%0], %1;" :: "r"(bar), "r"(cnt) : "memory");
}
__device__ __forceinline__ void mbar_expect_tx(uint32_t bar, uint32_t bytes) {
    asm volatile("mbarrier.arrive.expect_tx.shared::cta.b64 _, [%0], %1;" :: "r"(bar), "r"(bytes) : "memory");
}
__device__ __forceinline__ void mbar_arrive(uint32_t bar) {
    asm volatile("mbarrier.arrive.shared::cta.b64 _, [%0];" :: "r"(bar) : "memory");
}
__device__ __forceinline__ bool mbar_test(uint32_t bar, uint32_t parity) {
    uint32_t ok;
    asm volatile("{\n.reg .pred p;\nmbarrier.test_wait.parity.shared::cta.b64 p, [%1], %2;\nselp.u32 %0, 1, 0, p;\n}"
                 : "=r"(ok) : "r"(bar), "r"(parity) : "memory");
    return ok != 0;
}
__device__ __forceinline__ void mbar_wait(uint32_t bar, uint32_t parity) {
    asm volatile(
        "{\n"
        ".reg .pred p, q;\n"
        ".reg .u32 c;\n"
        "mov.u32 c, 0;\n"
        "LAB_WAIT:\n"
        "mbarrier.try_wait.parity.shared::cta.b64 p, [%0], %1;\n"
        "@p bra LAB_DONE;\n"
        "add.u32 c, c, 1;\n"
        "setp.lt.u32 q, c, 0x1000000;\n"
        "@q bra LAB_WAIT;\n"
        "trap;\n"
        "LAB_DONE:\n"
        "}\n" :: "r"(bar), "r"(parity) : "memory");
}
template <int ID, int N> __device__ __forceinline__ void bar_sync() { asm volatile("bar.sync %0, %1;" :: "n"(ID), "n"(N) : "memory"); }
template <int ID, int N> __device__ __forceinline__ void bar_arrive() { asm volatile("bar.arrive %0, %1;" :: "n"(ID), "n"(N) : "memory"); }
__device__ __forceinline__ void tma_tile(uint32_t dst, const CUtensorMap* tm, int row, uint32_t bar) {
    asm volatile("cp.async.bulk.tensor.3d.shared::cluster.global.mbarrier::complete_tx::bytes [%0], [%1, {%3, %4, %3}], [%2];"
                 :: "r"(dst), "l"(tm), "r"(bar), "r"(0), "r"(row) : "memory");
}
__device__ __forceinline__ void ldsm4(uint32_t (&r)[4], uint32_t addr) {
    asm volatile("ldmatrix.sync.aligned.m8n8.x4.shared.b16 {%0,%1,%2,%3}, [%4];"
                 : "=r"(r[0]), "=r"(r[1]), "=r"(r[2]), "=r"(r[3]) : "r"(addr));
}
__device__ __forceinline__ void ldsm4t(uint32_t (&r)[4], uint32_t addr) {
    asm volatile("ldmatrix.sync.aligned.m8n8.x4.trans.shared.b16 {%0,%1,%2,%3}, [%4];"
                 : "=r"(r[0]), "=r"(r[1]), "=r"(r[2]), "=r"(r[3]) : "r"(addr));
}
__device__ __forceinline__ void mma16816(float (&d)[4], uint32_t a0, uint32_t a1, uint32_t a2, uint32_t a3, uint32_t b0, uint32_t b1) {
    asm volatile("mma.sync.aligned.m16n8k16.row.col.f32.bf16.bf16.f32 {%0,%1,%2,%3}, {%4,%5,%6,%7}, {%8,%9}, {%0,%1,%2,%3};"
                 : "+f"(d[0]), "+f"(d[1]), "+f"(d[2]), "+f"(d[3]) : "r"(a0), "r"(a1), "r"(a2), "r"(a3), "r"(b0), "r"(b1));
}
__device__ __forceinline__ void sts2(uint32_t a, float x, float y) { asm volatile("st.shared.v2.f32 [%0], {%1,%2};" :: "r"(a), "f"(x), "f"(y) : "memory"); }
__device__ __forceinline__ void sts4(uint32_t a, float x, float y, float z, float w) {
    asm volatile("st.shared.v4.f32 [%0], {%1,%2,%3,%4};" :: "r"(a), "f"(x), "f"(y), "f"(z), "f"(w) : "memory");
}
__device__ __forceinline__ void lds4(float (&v)[4], uint32_t a) {
    asm volatile("ld.shared.v4.f32 {%0,%1,%2,%3}, [%4];" : "=f"(v[0]), "=f"(v[1]), "=f"(v[2]), "=f"(v[3]) : "r"(a) : "memory");
}
__device__ __forceinline__ float ex2(float x) { float y; asm("ex2.approx.ftz.f32 %0, %1;" : "=f"(y) : "f"(x)); return y; }
__device__ __forceinline__ float rcp(float x) { float y; asm("rcp.approx.ftz.f32 %0, %1;" : "=f"(y) : "f"(x)); return y; }
__device__ __forceinline__ float expdiff(float a, float b) { return ex2((a - b) * kLog2e); }
__device__ __forceinline__ float sel(uint32_t c, float a, float b) {
    float r; asm("{\n.reg .pred p;\nsetp.ne.u32 p, %3, 0;\nselp.f32 %0, %1, %2, p;\n}" : "=f"(r) : "f"(a), "f"(b), "r"(c)); return r;
}
__device__ __forceinline__ uint32_t pack_bf16(float lo, float hi) {
    uint32_t r; asm("cvt.rn.bf16x2.f32 %0, %1, %2;" : "=r"(r) : "f"(hi), "f"(lo)); return r;
}
__device__ __forceinline__ float bf_lo(uint32_t v) { return __uint_as_float(v << 16); }
__device__ __forceinline__ float bf_hi(uint32_t v) { return __uint_as_float(v & 0xffff0000u); }
__device__ __forceinline__ float bf_round(float x) { return __bfloat162float(__float2bfloat16(x)); }
__device__ __forceinline__ uint32_t scale_scores(float a, float b) {
    const uint32_t r = pack_bf16(a, b);
    return pack_bf16(bf_lo(r) * kScale, bf_hi(r) * kScale);
}
__device__ __forceinline__ void st_bf16(__nv_bfloat16* p, float v) {
    asm volatile("{\n.reg .b16 h;\ncvt.rn.bf16.f32 h, %1;\nst.global.b16 [%0], h;\n}" :: "l"(p), "f"(v) : "memory");
}
__device__ __forceinline__ void st_word(uint64_t* p, uint64_t v) {
    asm volatile("st.relaxed.gpu.global.b64 [%0], %1;" :: "l"(p), "l"(v) : "memory");
}
__device__ __forceinline__ void ld_word_if(uint64_t& a, const uint64_t* p, bool pred) {
    asm volatile("{\n.reg .pred p;\nsetp.ne.u32 p, %2, 0;\n@p ld.relaxed.gpu.global.b64 %0, [%1];\n}"
                 : "+l"(a) : "l"(p), "r"((uint32_t)pred) : "memory");
}
__device__ __forceinline__ void ld_word2_if(uint64_t& a, uint64_t& b, const uint64_t* p, bool pred) {
    asm volatile("{\n.reg .pred p;\nsetp.ne.u32 p, %3, 0;\n@p ld.relaxed.gpu.global.v2.b64 {%0, %1}, [%2];\n}"
                 : "+l"(a), "+l"(b) : "l"(p), "r"((uint32_t)pred) : "memory");
}
__device__ __forceinline__ uint64_t make_word(float lo, float hi) {
    uint32_t u = __float_as_uint(lo);
    if (u == 0u) u = 0x80000000u;
    return ((uint64_t)__float_as_uint(hi) << 32) | u;
}
__device__ __forceinline__ float word_lo(uint64_t w) { return __uint_as_float((uint32_t)w); }
__device__ __forceinline__ float word_hi(uint64_t w) { return __uint_as_float((uint32_t)(w >> 32)); }
__device__ __forceinline__ bool missing(uint64_t w) { return (uint32_t)w == 0u; }

__global__ void __launch_bounds__(kThreads, 1)
tree_attn_decode_kernel(const __grid_constant__ CUtensorMap tmK, const __grid_constant__ CUtensorMap tmV,
                        const __nv_bfloat16* __restrict__ q, const __nv_bfloat16* __restrict__ k_cache,
                        const __nv_bfloat16* __restrict__ k_tree, const __nv_bfloat16* __restrict__ v_tree,
                        const __nv_bfloat16* __restrict__ mask, __nv_bfloat16* __restrict__ out,
                        uint64_t* __restrict__ mailbox, int pace_off_ns, int pace_tau_q8)
{
    const int row0 = blockIdx.x * kKeysPerCta;
    if (threadIdx.x == 0)
        asm volatile("cp.async.bulk.prefetch.L2.global [%0], %1;" :: "l"(k_cache + (size_t)row0 * kD), "n"(3 * kSlotBytes) : "memory");

    extern __shared__ uint8_t smem_raw[];
    const uint32_t sbase = (smem_u32(smem_raw) + 1023) & ~1023u;
    const uint32_t aux = sbase + kNS * kSlotBytes;
    const uint32_t full = aux + kOffBar, empty = full + kNS * 8;

    uint32_t t0 = 0;
    if (threadIdx.x == kNC) {
        t0 = timer_ns();
#pragma unroll
        for (int s = 0; s < kNS; s++) mbar_init(full + s * 8, 1);
        asm volatile("fence.mbarrier_init.release.cluster;" ::: "memory");
#pragma unroll
        for (int i = 0; i < 3; i++) {
            mbar_expect_tx(full + i * 8, kSlotBytes);
            tma_tile(sbase + i * kSlotBytes, &tmK, row0 + i * kTile, full + i * 8);
        }
#pragma unroll
        for (int s = 0; s < kNS; s++) mbar_init(empty + s * 8, kNW);
    }
    const int warp = threadIdx.x >> 5, lane = threadIdx.x & 31;
    const int pair = blockIdx.x >> 2;
    const bool merger = (blockIdx.x & 3) == kSplit - 1;

    if (warp == kNW) {
        __syncwarp();
        bar_arrive<1, kThreads>();
        uint64_t* stat = mailbox + (size_t)pair * kSplit * kBoxWords + kD;
        asm volatile("" : "+l"(stat));
        uint64_t wm[3] = {0ull, 0ull, 0ull}, wl[3] = {0ull, 0ull, 0ull};
        if (lane == 0) {
            const int off = pace_off_ns + (merger ? kMergerLagNs : 0);
#pragma unroll 1
            for (int i = 3; i < kNL; i++) {
                const int s = i % kNS;
                mbar_wait(empty + s * 8, ((i / kNS) & 1) ^ 1);
                if (i >= kFreeLoads) {
                    const uint32_t due = (uint32_t)(off + (((i - kFreeLoads) * pace_tau_q8) >> 8));
                    const int j = i - kMinInflight;
                    while (timer_ns() - t0 < due && !mbar_test(full + (j % kNS) * 8, (j / kNS) & 1)) { }
                }
                if (i == kNL - 1) {
#pragma unroll
                    for (int y = 0; y < 3; y++) ld_word2_if(wm[y], wl[y], stat + y * kBoxWords, merger);
                }
                const int j = i - kLead;
                const bool is_k = i < kLead || (i < kNL - kLead && !(j & 1));
                const int tile = i < kLead ? i : i >= kNL - kLead ? i - kNT : is_k ? kLead + (j >> 1) : (j >> 1);
                mbar_expect_tx(full + s * 8, kSlotBytes);
                tma_tile(sbase + s * kSlotBytes, is_k ? &tmK : &tmV, row0 + tile * kTile, full + s * 8);
            }
        }
        if (!merger) return;
        if (lane == 0) {
#pragma unroll 1
            for (int it = 0;; it++) {
                bool miss[3];
#pragma unroll
                for (int y = 0; y < 3; y++) miss[y] = missing(wm[y]) || missing(wl[y]);
                if (!(miss[0] || miss[1] || miss[2])) break;
                if (it > (1 << 22)) __trap();
#pragma unroll
                for (int y = 0; y < 3; y++) ld_word2_if(wm[y], wl[y], stat + y * kBoxWords, miss[y]);
            }
        }
        __syncwarp();
        if (lane < 12) st_word(stat + (lane >> 2) * kBoxWords + (lane & 3), 0ull);
        bar_sync<3, 64>();
        if (lane == 0) {
            float own[4], c0[4], c1[4];
            lds4(own, aux + kOffStat);
            const float M0 = fmaxf(fmaxf(own[0], word_lo(wm[0])), fmaxf(word_lo(wm[1]), word_lo(wm[2])));
            const float M1 = fmaxf(fmaxf(own[1], word_hi(wm[0])), fmaxf(word_hi(wm[1]), word_hi(wm[2])));
#pragma unroll
            for (int y = 0; y < 3; y++) {
                c0[y] = expdiff(word_lo(wm[y]), M0) * word_lo(wl[y]);
                c1[y] = expdiff(word_hi(wm[y]), M1) * word_hi(wl[y]);
            }
            c0[3] = expdiff(own[0], M0) * own[2];
            c1[3] = expdiff(own[1], M1) * own[3];
            const float r0 = rcp((c0[0] + c0[1]) + (c0[2] + c0[3])), r1 = rcp((c1[0] + c1[1]) + (c1[2] + c1[3]));
            sts4(aux + kOffWgt, c0[0] * r0, c0[1] * r0, c0[2] * r0, c0[3] * r0);
            sts4(aux + kOffWgt + 16, c1[0] * r1, c1[1] * r1, c1[2] * r1, c1[3] * r1);
        }
        __syncwarp();
        bar_arrive<4, kThreads>();
        return;
    }

    const int g = lane >> 2, t = lane & 3;

    uint32_t qa[8][2];
    {
        const uint32_t* qp = reinterpret_cast<const uint32_t*>(q + (size_t)(pair * 2 + (g & 1)) * kD);
#pragma unroll
        for (int j = 0; j < 8; j++) { qa[j][0] = __ldg(qp + j * 8 + t); qa[j][1] = __ldg(qp + j * 8 + 4 + t); }
    }
    const int mydim = warp * 32 + (t >> 1) * 16 + (t & 1) * 8 + g;
    uint64_t* box = mailbox + (size_t)(merger ? pair * kSplit : blockIdx.x) * kBoxWords;
    uint64_t* slot = box + mydim;
    __nv_bfloat16* op = out + (size_t)pair * 2 * kD + mydim;
    asm volatile("" : "+l"(box), "+l"(slot), "+l"(op));

    float acc[8][4];
    float m = -INFINITY, l = 0.f;
#pragma unroll
    for (int j = 0; j < 8; j++) { acc[j][0] = acc[j][1] = acc[j][2] = acc[j][3] = 0.f; }
    if (merger && warp == 0) {
        const uint32_t* kp = reinterpret_cast<const uint32_t*>(k_tree + (size_t)pair * kD);
        const __nv_bfloat16* vp = v_tree + (size_t)pair * kD;
        float s4[4] = {0.f, 0.f, 0.f, 0.f};
#pragma unroll
        for (int j = 0; j < 8; j++) {
            mma16816(s4, qa[j][0], 0u, qa[j][1], 0u, __ldg(kp + j * 8 + t), __ldg(kp + j * 8 + 4 + t));
            acc[j][0] = acc[j][1] = __bfloat162float(vp[j * 16 + g]);
            acc[j][2] = acc[j][3] = __bfloat162float(vp[j * 16 + 8 + g]);
        }
        const float keep = __bfloat162float(mask[pair / kHkv]);
        m = bf_round(bf_lo(scale_scores(s4[0], s4[1])) + bf_round(bf_round(1.0f - keep) * -1000000000.0f));
        l = (t == 0) ? 1.f : 0.f;
    }

    const int r7 = lane & 7, mi = lane >> 3;
    const uint32_t ka0 = sbase + (uint32_t)(warp * 16 + r7) * 128 + ((mi ^ r7) << 4);
    const uint32_t ka1 = sbase + (uint32_t)(warp * 16 + r7) * 128 + (((4 + mi) ^ r7) << 4);
    uint32_t va[4];
#pragma unroll
    for (int jj = 0; jj < 4; jj++)
        va[jj] = sbase + (uint32_t)(warp * 16 + (mi >> 1) * 8 + r7) * 128 + (((jj * 2 + (mi & 1)) ^ r7) << 4);

    bar_sync<1, kThreads>();

    int s = 0, ph = 0;
    auto release = [&]() {
        __syncwarp();
        if (lane == 0) mbar_arrive(empty + s * 8);
        if (++s == kNS) { s = 0; ph ^= 1; }
    };
    auto probs = [&](uint32_t s01, uint32_t s23, float (&p)[4]) {
        p[0] = expdiff(bf_lo(s01), m); p[1] = expdiff(bf_hi(s01), m);
        p[2] = expdiff(bf_lo(s23), m); p[3] = expdiff(bf_hi(s23), m);
        l += (p[0] + p[1]) + (p[2] + p[3]);
    };

    uint32_t fifo[kLead + 1][2];
#pragma unroll
    for (int x = 0; x <= kLead; x++) fifo[x][0] = fifo[x][1] = 0u;
#pragma unroll 1
    for (int n = -kLead;; n++) {
#pragma unroll
        for (int x = 0; x < kLead; x++) { fifo[x][0] = fifo[x + 1][0]; fifo[x][1] = fifo[x + 1][1]; }
        {
            uint32_t a0 = ka0 + s * kSlotBytes, a1 = ka1 + s * kSlotBytes;
            asm volatile("" : "+r"(a0), "+r"(a1));
            mbar_wait(full + s * 8, ph);
            float sc[2][2][4];
#pragma unroll
            for (int u = 0; u < 2; u++)
#pragma unroll
                for (int c = 0; c < 2; c++) sc[u][c][0] = sc[u][c][1] = sc[u][c][2] = sc[u][c][3] = 0.f;
#pragma unroll
            for (int qd = 0; qd < 4; qd++) {
#pragma unroll
                for (int u = 0; u < 2; u++) {
                    uint32_t r[4];
                    ldsm4(r, ((qd & 1) ? a1 : a0) + u * 1024 + (qd >> 1) * kHalf);
                    mma16816(sc[u][0], qa[2 * qd][0], 0u, qa[2 * qd][1], 0u, r[0], r[1]);
                    mma16816(sc[u][1], qa[2 * qd + 1][0], 0u, qa[2 * qd + 1][1], 0u, r[2], r[3]);
                }
            }
            release();
            const uint32_t s01 = scale_scores(sc[0][0][0] + sc[0][1][0], sc[0][0][1] + sc[0][1][1]);
            const uint32_t s23 = scale_scores(sc[1][0][0] + sc[1][1][0], sc[1][0][1] + sc[1][1][1]);
            fifo[kLead][0] = s01; fifo[kLead][1] = s23;
            float mx = fmaxf(fmaxf(bf_lo(s01), bf_hi(s01)), fmaxf(bf_lo(s23), bf_hi(s23)));
            mx = fmaxf(mx, __shfl_xor_sync(0xffffffffu, mx, 1));
            mx = fmaxf(mx, __shfl_xor_sync(0xffffffffu, mx, 2));
            if (__any_sync(0xffffffffu, mx > m)) {
                const float mn = fmaxf(m, mx);
                const float f = expdiff(m, mn), fo = __shfl_xor_sync(0xffffffffu, f, 4);
                const float f0 = (g & 1) ? fo : f, f1 = (g & 1) ? f : fo;
                m = mn; l *= f;
#pragma unroll
                for (int j = 0; j < 8; j++) { acc[j][0] *= f0; acc[j][1] *= f1; acc[j][2] *= f0; acc[j][3] *= f1; }
            }
        }
        if (n == kNT - kLead - 1) break;
        if (n >= 0) {
            float p[4];
            probs(fifo[0][0], fifo[0][1], p);
            const uint32_t b0 = pack_bf16(p[0], p[1]), b1 = pack_bf16(p[2], p[3]);
            uint32_t a[4];
#pragma unroll
            for (int jj = 0; jj < 4; jj++) a[jj] = va[jj] + s * kSlotBytes;
            asm volatile("" : "+r"(a[0]), "+r"(a[1]), "+r"(a[2]), "+r"(a[3]));
            mbar_wait(full + s * 8, ph);
#pragma unroll
            for (int j = 0; j < 8; j++) {
                uint32_t r[4];
                ldsm4t(r, a[j & 3] + (j >> 2) * kHalf);
                mma16816(acc[j], r[0], r[1], r[2], r[3], b0, b1);
            }
            release();
        }
    }

    float c[2][4];
    uint32_t pb[kLead + 1][kNW][2];
    {
#pragma unroll
        for (int x = 0; x <= kLead; x++) {
            float p[4];
            probs(fifo[x][0], fifo[x][1], p);
            asm volatile("st.shared.v2.b32 [%0], {%1,%2};"
                         :: "r"(aux + kOffSc + (x * kNW + warp) * 256 + lane * 8), "r"(fifo[x][0]), "r"(fifo[x][1]) : "memory");
        }
        float lr = l + __shfl_xor_sync(0xffffffffu, l, 1);
        lr += __shfl_xor_sync(0xffffffffu, lr, 2);
        if (t == 0) {
#pragma unroll
            for (int j = 0; j < 8; j++) sts4(aux + kOffAcc + warp * 1024 + j * 128 + g * 16, acc[j][0], acc[j][1], acc[j][2], acc[j][3]);
            if (g < 2) sts2(aux + kOffMl + warp * 16 + g * 8, m, lr);
        }
        bar_sync<2, kNC>();
        float mm[kNW][4];
        float M0 = -INFINITY, M1 = -INFINITY;
#pragma unroll
        for (int w = 0; w < kNW; w++) {
            lds4(mm[w], aux + kOffMl + w * 16);
            M0 = fmaxf(M0, mm[w][0]); M1 = fmaxf(M1, mm[w][2]);
        }
        float f0[kNW], f1[kNW], L0 = 0.f, L1 = 0.f;
#pragma unroll
        for (int w = 0; w < kNW; w++) {
            f0[w] = expdiff(mm[w][0], M0); f1[w] = expdiff(mm[w][2], M1);
            L0 = fmaf(f0[w], mm[w][1], L0); L1 = fmaf(f1[w], mm[w][3], L1);
        }
        if (warp == 0) {
            if (!merger) {
                if (lane < 4) st_word(box + kD + lane, (lane & 1) ? make_word(L0, L1) : make_word(M0, M1));
            } else {
                if (lane == 0) sts4(aux + kOffStat, M0, M1, L0, L1);
                __syncwarp();
                bar_arrive<3, 64>();
            }
        }
        const float r0 = rcp(L0), r1 = rcp(L1);
#pragma unroll
        for (int jj = 0; jj < 2; jj++) {
            c[jj][0] = c[jj][1] = c[jj][2] = c[jj][3] = 0.f;
#pragma unroll
            for (int w = 0; w < kNW; w++) {
                float v[4];
                lds4(v, aux + kOffAcc + w * 1024 + (warp * 2 + jj) * 128 + g * 16);
                c[jj][0] = fmaf(f0[w], v[0], c[jj][0]); c[jj][1] = fmaf(f1[w], v[1], c[jj][1]);
                c[jj][2] = fmaf(f0[w], v[2], c[jj][2]); c[jj][3] = fmaf(f1[w], v[3], c[jj][3]);
            }
            c[jj][0] *= r0; c[jj][1] *= r1; c[jj][2] *= r0; c[jj][3] *= r1;
        }
        const float Mh = (g & 1) ? M1 : M0, rh = (g & 1) ? r1 : r0;
#pragma unroll
        for (int x = 0; x <= kLead; x++)
#pragma unroll
            for (int w = 0; w < kNW; w++) {
                uint32_t s01, s23;
                asm volatile("ld.shared.v2.b32 {%0,%1}, [%2];"
                             : "=r"(s01), "=r"(s23) : "r"(aux + kOffSc + (x * kNW + w) * 256 + lane * 8) : "memory");
                pb[x][w][0] = pack_bf16(expdiff(bf_lo(s01), Mh) * rh, expdiff(bf_hi(s01), Mh) * rh);
                pb[x][w][1] = pack_bf16(expdiff(bf_lo(s23), Mh) * rh, expdiff(bf_hi(s23), Mh) * rh);
            }
    }

    uint32_t la[2];
#pragma unroll
    for (int jj = 0; jj < 2; jj++)
        la[jj] = sbase + (warp >> 1) * kHalf + (uint32_t)((mi >> 1) * 8 + r7) * 128 + ((((warp & 1) * 4 + jj * 2 + (mi & 1)) ^ r7) << 4);
    uint64_t ow[3] = {0ull, 0ull, 0ull};
    asm volatile("" : "+r"(la[0]), "+r"(la[1]), "+l"(ow[0]), "+l"(ow[1]), "+l"(ow[2]));
    float w0[4], w1[4];
    float cb[2][4] = {{0.f, 0.f, 0.f, 0.f}, {0.f, 0.f, 0.f, 0.f}};
#pragma unroll
    for (int x = 0; x <= kLead; x++) {
        constexpr int kFirst = kNL - 1 - kLead;
        const int sl = (kFirst + x) % kNS;
        if (x == kLead - 3 && !merger) st_word(slot, 0ull);
        if (x == kLead && merger) {
            bar_sync<4, kThreads>();
            lds4(w0, aux + kOffWgt);
            lds4(w1, aux + kOffWgt + 16);
        }
        mbar_wait(full + sl * 8, ((kFirst + x) / kNS) & 1);
        if (x == kLead) {
#pragma unroll
            for (int y = 0; y < 3; y++) ld_word_if(ow[y], slot + y * kBoxWords, merger);
        }
        uint32_t r[kNW][2][4];
#pragma unroll
        for (int k = 0; k < kNW; k++)
#pragma unroll
            for (int jj = 0; jj < 2; jj++) ldsm4t(r[k][jj], la[jj] + sl * kSlotBytes + k * 2048);
#pragma unroll
        for (int k = 0; k < kNW; k++)
#pragma unroll
            for (int jj = 0; jj < 2; jj++)
                mma16816((k & 1) ? cb[jj] : c[jj], r[k][jj][0], r[k][jj][1], r[k][jj][2], r[k][jj][3], pb[x][k][0], pb[x][k][1]);
    }
    const uint32_t t1 = t & 1, t2 = t & 2;
    const float o0 = sel(t2, sel(t1, c[1][2], c[1][0]), sel(t1, c[0][2], c[0][0])) + sel(t2, sel(t1, cb[1][2], cb[1][0]), sel(t1, cb[0][2], cb[0][0]));
    const float o1 = sel(t2, sel(t1, c[1][3], c[1][1]), sel(t1, c[0][3], c[0][1])) + sel(t2, sel(t1, cb[1][3], cb[1][1]), sel(t1, cb[0][3], cb[0][1]));
    if (!merger) {
        st_word(slot, make_word(o0, o1));
        return;
    }
    const float a0 = w0[3] * o0, a1 = w1[3] * o1;
#pragma unroll 1
    for (int it = 0; missing(ow[0]) || missing(ow[1]) || missing(ow[2]); it++) {
        if (it > (1 << 22)) __trap();
#pragma unroll
        for (int y = 0; y < 3; y++) ld_word_if(ow[y], slot + y * kBoxWords, missing(ow[y]));
    }
    st_bf16(op, fmaf(w0[0], word_lo(ow[0]), a0) + fmaf(w0[1], word_lo(ow[1]), w0[2] * word_lo(ow[2])));
    st_bf16(op + kD, fmaf(w1[0], word_hi(ow[0]), a1) + fmaf(w1[1], word_hi(ow[1]), w1[2] * word_hi(ow[2])));
#pragma unroll
    for (int y = 0; y < 3; y++) st_word(slot + y * kBoxWords, 0ull);
}

typedef CUresult (*EncodeTiledFn)(CUtensorMap*, CUtensorMapDataType, cuuint32_t, void*, const cuuint64_t*, const cuuint64_t*,
                                  const cuuint32_t*, const cuuint32_t*, CUtensorMapInterleave, CUtensorMapSwizzle,
                                  CUtensorMapL2promotion, CUtensorMapFloatOOBfill);

CUtensorMap make_kv_map(EncodeTiledFn encode, void* base) {
    CUtensorMap m;
    const cuuint64_t dims[3] = {64, (cuuint64_t)kPairs * kC, 2};
    const cuuint64_t strides[2] = {256, 128};
    const cuuint32_t box[3] = {64, (cuuint32_t)kTile, 2};
    const cuuint32_t elem[3] = {1, 1, 1};
    encode(&m, CU_TENSOR_MAP_DATA_TYPE_BFLOAT16, 3, base, dims, strides, box, elem, CU_TENSOR_MAP_INTERLEAVE_NONE,
           CU_TENSOR_MAP_SWIZZLE_128B, CU_TENSOR_MAP_L2_PROMOTION_L2_256B, CU_TENSOR_MAP_FLOAT_OOB_FILL_NONE);
    return m;
}

}

extern "C" void kernel_launch(void* const* d_in, const int* in_sizes, int n_in, void* d_out, int out_size) {
    (void)in_sizes; (void)n_in; (void)out_size;
    static EncodeTiledFn encode = nullptr;
    static void* mailbox = nullptr;
    static int pace_off_ns = 0, pace_tau_q8 = 0;
    if (!encode) {
        cudaDriverEntryPointQueryResult qr;
        cudaGetDriverEntryPoint("cuTensorMapEncodeTiled", (void**)&encode, cudaEnableDefault, &qr);
        cudaFuncSetAttribute(tree_attn_decode_kernel, cudaFuncAttributeMaxDynamicSharedMemorySize, kSmemBytes);
        cudaGetSymbolAddress(&mailbox, g_mailbox);
        int dev = 0, mem_khz = 0, bus_bits = 0;
        cudaGetDevice(&dev);
        cudaDeviceGetAttribute(&mem_khz, cudaDevAttrMemoryClockRate, dev);
        cudaDeviceGetAttribute(&bus_bits, cudaDevAttrGlobalMemoryBusWidth, dev);
        const double bytes_per_ns = 2.0 * mem_khz * 1e-6 * bus_bits / 8.0;
        if (bytes_per_ns > 0.0) {
            const double tau = (double)kPairs * kSplit * kSlotBytes / (0.9595 * bytes_per_ns);
            pace_tau_q8 = (int)(tau * 256.0);
            pace_off_ns = (int)(2.0 * tau);
        }
    }
    const CUtensorMap tmK = make_kv_map(encode, d_in[1]);
    const CUtensorMap tmV = make_kv_map(encode, d_in[2]);
    tree_attn_decode_kernel<<<kPairs * kSplit, kThreads, kSmemBytes>>>(
        tmK, tmV, (const __nv_bfloat16*)d_in[0], (const __nv_bfloat16*)d_in[1], (const __nv_bfloat16*)d_in[3],
        (const __nv_bfloat16*)d_in[4], (const __nv_bfloat16*)d_in[5], (__nv_bfloat16*)d_out, (uint64_t*)mailbox,
        pace_off_ns, pace_tau_q8);
}
```

```cpp
#include <cuda_runtime.h>
#include <cuda_bf16.h>
#include <cuda.h>
#include <stdint.h>

namespace {

constexpr int kB = 2, kHkv = 16, kC = 8192, kD = 128;
constexpr int kPairs = kB * kHkv;
constexpr int kSplit = 4;
constexpr int kKeysPerCta = kC / kSplit;
constexpr int kTile = 64;
constexpr int kNW = kTile / 16;
constexpr int kNC = kNW * 32;
constexpr int kThreads = kNC + 32;
constexpr int kNS = 8;
constexpr int kNT = kKeysPerCta / kTile;
constexpr int kNL = 2 * kNT;
constexpr int kLead = 10;
constexpr int kFin = 4;
constexpr int kEarly = kLead + 1 - kFin;
constexpr int kSlotBytes = kTile * kD * 2;
constexpr uint32_t kHalf = kTile * 128;
constexpr int kFreeLoads = 4;
constexpr int kMinInflight = 2;
constexpr float kScale = 0.08838834764831845f;
constexpr float kLog2e = 1.4426950408889634f;
constexpr uint32_t kOffAcc = 0;
constexpr uint32_t kOffMl = kOffAcc + kNW * 1024;
constexpr uint32_t kOffP = kOffMl + kNW * 16;
constexpr uint32_t kOffBar = kOffP + kSplit * 1024;
constexpr int kSmemBytes = 1024   + kNS * kSlotBytes + kOffBar + 2 * kNS * 8;
static_assert(kNC == kD && kSplit == 4 && kNW == 4 && kFin == 4, "layout assumptions");
static_assert(kLead >= 3 && kEarly >= 3 && kFin <= kNS, "load order assumptions");

constexpr int kSecScore = 0;
constexpr int kSecStat = 128;
constexpr int kSecOut = 144;
constexpr int kSecWords = 176;
constexpr int kBoxWords = 3 * kSecWords;
__device__ __align__(128) uint64_t g_inbox[kPairs * kSplit * kBoxWords];

__device__ __forceinline__ uint32_t smem_u32(const void* p) { return (uint32_t)__cvta_generic_to_shared(p); }
__device__ __forceinline__ uint32_t timer_ns() { uint32_t t; asm volatile("mov.u32 %0, %globaltimer_lo;" : "=r"(t)); return t; }
__device__ __forceinline__ void mbar_init(uint32_t bar, uint32_t cnt) {
    asm volatile("mbarrier.init.shared::cta.b64 [%0], %1;" :: "r"(bar), "r"(cnt) : "memory");
}
__device__ __forceinline__ void mbar_expect_tx(uint32_t bar, uint32_t bytes) {
    asm volatile("mbarrier.arrive.expect_tx.shared::cta.b64 _, [%0], %1;" :: "r"(bar), "r"(bytes) : "memory");
}
__device__ __forceinline__ void mbar_arrive(uint32_t bar) {
    asm volatile("mbarrier.arrive.shared::cta.b64 _, [%0];" :: "r"(bar) : "memory");
}
__device__ __forceinline__ bool mbar_test(uint32_t bar, uint32_t parity) {
    uint32_t ok;
    asm volatile("{\n.reg .pred p;\nmbarrier.test_wait.parity.shared::cta.b64 p, [%1], %2;\nselp.u32 %0, 1, 0, p;\n}"
                 : "=r"(ok) : "r"(bar), "r"(parity) : "memory");
    return ok != 0;
}
__device__ __forceinline__ void mbar_wait(uint32_t bar, uint32_t parity) {
    asm volatile(
        "{\n"
        ".reg .pred p, q;\n"
        ".reg .u32 c;\n"
        "mov.u32 c, 0;\n"
        "LAB_WAIT:\n"
        "mbarrier.try_wait.parity.shared::cta.b64 p, [%0], %1;\n"
        "@p bra LAB_DONE;\n"
        "add.u32 c, c, 1;\n"
        "setp.lt.u32 q, c, 0x1000000;\n"
        "@q bra LAB_WAIT;\n"
        "trap;\n"
        "LAB_DONE:\n"
        "}\n" :: "r"(bar), "r"(parity) : "memory");
}
template <int ID, int N> __device__ __forceinline__ void bar_sync() { asm volatile("bar.sync %0, %1;" :: "n"(ID), "n"(N) : "memory"); }
template <int ID, int N> __device__ __forceinline__ void bar_arrive() { asm volatile("bar.arrive %0, %1;" :: "n"(ID), "n"(N) : "memory"); }
__device__ __forceinline__ void tma_tile(uint32_t dst, const CUtensorMap* tm, int row, uint32_t bar) {
    asm volatile("cp.async.bulk.tensor.3d.shared::cluster.global.mbarrier::complete_tx::bytes [%0], [%1, {%3, %4, %3}], [%2];"
                 :: "r"(dst), "l"(tm), "r"(bar), "r"(0), "r"(row) : "memory");
}
__device__ __forceinline__ void tma_strip(uint32_t dst, const CUtensorMap* tm, int col, int row, uint32_t bar) {
    asm volatile("cp.async.bulk.tensor.2d.shared::cluster.global.mbarrier::complete_tx::bytes [%0], [%1, {%3, %4}], [%2];"
                 :: "r"(dst), "l"(tm), "r"(bar), "r"(col), "r"(row) : "memory");
}
__device__ __forceinline__ void ldsm4(uint32_t (&r)[4], uint32_t addr) {
    asm volatile("ldmatrix.sync.aligned.m8n8.x4.shared.b16 {%0,%1,%2,%3}, [%4];"
                 : "=r"(r[0]), "=r"(r[1]), "=r"(r[2]), "=r"(r[3]) : "r"(addr));
}
__device__ __forceinline__ void ldsm4t(uint32_t (&r)[4], uint32_t addr) {
    asm volatile("ldmatrix.sync.aligned.m8n8.x4.trans.shared.b16 {%0,%1,%2,%3}, [%4];"
                 : "=r"(r[0]), "=r"(r[1]), "=r"(r[2]), "=r"(r[3]) : "r"(addr));
}
__device__ __forceinline__ void mma16816(float (&d)[4], uint32_t a0, uint32_t a1, uint32_t a2, uint32_t a3, uint32_t b0, uint32_t b1) {
    asm volatile("mma.sync.aligned.m16n8k16.row.col.f32.bf16.bf16.f32 {%0,%1,%2,%3}, {%4,%5,%6,%7}, {%8,%9}, {%0,%1,%2,%3};"
                 : "+f"(d[0]), "+f"(d[1]), "+f"(d[2]), "+f"(d[3]) : "r"(a0), "r"(a1), "r"(a2), "r"(a3), "r"(b0), "r"(b1));
}
__device__ __forceinline__ void sts2(uint32_t a, uint32_t x, uint32_t y) {
    asm volatile("st.shared.v2.b32 [%0], {%1,%2};" :: "r"(a), "r"(x), "r"(y) : "memory");
}
__device__ __forceinline__ void lds2(uint32_t& x, uint32_t& y, uint32_t a) {
    asm volatile("ld.shared.v2.b32 {%0,%1}, [%2];" : "=r"(x), "=r"(y) : "r"(a) : "memory");
}
__device__ __forceinline__ void sts4(uint32_t a, const float (&v)[4]) {
    asm volatile("st.shared.v4.f32 [%0], {%1,%2,%3,%4};" :: "r"(a), "f"(v[0]), "f"(v[1]), "f"(v[2]), "f"(v[3]) : "memory");
}
__device__ __forceinline__ void lds4(float (&v)[4], uint32_t a) {
    asm volatile("ld.shared.v4.f32 {%0,%1,%2,%3}, [%4];" : "=f"(v[0]), "=f"(v[1]), "=f"(v[2]), "=f"(v[3]) : "r"(a) : "memory");
}
__device__ __forceinline__ float ex2(float x) { float y; asm("ex2.approx.ftz.f32 %0, %1;" : "=f"(y) : "f"(x)); return y; }
__device__ __forceinline__ float rcp(float x) { float y; asm("rcp.approx.ftz.f32 %0, %1;" : "=f"(y) : "f"(x)); return y; }
__device__ __forceinline__ float expdiff(float a, float b) { return ex2((a - b) * kLog2e); }
__device__ __forceinline__ float sel(uint32_t c, float a, float b) {
    float r; asm("{\n.reg .pred p;\nsetp.ne.u32 p, %3, 0;\nselp.f32 %0, %1, %2, p;\n}" : "=f"(r) : "f"(a), "f"(b), "r"(c)); return r;
}
__device__ __forceinline__ uint32_t pack_bf16(float lo, float hi) {
    uint32_t r; asm("cvt.rn.bf16x2.f32 %0, %1, %2;" : "=r"(r) : "f"(hi), "f"(lo)); return r;
}
__device__ __forceinline__ float bf_lo(uint32_t v) { return __uint_as_float(v << 16); }
__device__ __forceinline__ float bf_hi(uint32_t v) { return __uint_as_float(v & 0xffff0000u); }
__device__ __forceinline__ float bf_round(float x) { return __bfloat162float(__float2bfloat16(x)); }
__device__ __forceinline__ uint32_t scale_scores(float a, float b) {
    const uint32_t r = pack_bf16(a, b);
    return pack_bf16(bf_lo(r) * kScale, bf_hi(r) * kScale);
}
__device__ __forceinline__ void st_bf16(__nv_bfloat16* p, float v) {
    asm volatile("{\n.reg .b16 h;\ncvt.rn.bf16.f32 h, %1;\nst.global.b16 [%0], h;\n}" :: "l"(p), "f"(v) : "memory");
}
__device__ __forceinline__ void st_word(uint64_t* p, uint64_t v) {
    asm volatile("st.relaxed.gpu.global.b64 [%0], %1;" :: "l"(p), "l"(v) : "memory");
}
__device__ __forceinline__ void ld_word_if(uint64_t& a, const uint64_t* p, bool pred) {
    asm volatile("{\n.reg .pred p;\nsetp.ne.u32 p, %2, 0;\n@p ld.relaxed.gpu.global.b64 %0, [%1];\n}"
                 : "+l"(a) : "l"(p), "r"((uint32_t)pred) : "memory");
}
__device__ __forceinline__ void ld_word2_if(uint64_t& a, uint64_t& b, const uint64_t* p, bool pred) {
    asm volatile("{\n.reg .pred p;\nsetp.ne.u32 p, %3, 0;\n@p ld.relaxed.gpu.global.v2.b64 {%0, %1}, [%2];\n}"
                 : "+l"(a), "+l"(b) : "l"(p), "r"((uint32_t)pred) : "memory");
}
__device__ __forceinline__ uint64_t make_word(uint32_t lo, uint32_t hi) {
    if (lo == 0u) lo = 0x80000000u;
    return ((uint64_t)hi << 32) | lo;
}
__device__ __forceinline__ uint64_t make_word(float lo, float hi) { return make_word(__float_as_uint(lo), __float_as_uint(hi)); }
__device__ __forceinline__ float word_lo(uint64_t w) { return __uint_as_float((uint32_t)w); }
__device__ __forceinline__ float word_hi(uint64_t w) { return __uint_as_float((uint32_t)(w >> 32)); }
__device__ __forceinline__ bool missing(uint64_t w) { return (uint32_t)w == 0u; }

__global__ void __launch_bounds__(kThreads, 1)
tree_attn_decode_kernel(const __grid_constant__ CUtensorMap tmK, const __grid_constant__ CUtensorMap tmV,
                        const __grid_constant__ CUtensorMap tmStrip,
                        const __nv_bfloat16* __restrict__ q, const __nv_bfloat16* __restrict__ k_cache,
                        const __nv_bfloat16* __restrict__ k_tree, const __nv_bfloat16* __restrict__ v_tree,
                        const __nv_bfloat16* __restrict__ mask, __nv_bfloat16* __restrict__ out,
                        uint64_t* __restrict__ inboxes, int pace_off_ns, int pace_tau_q8)
{
    const int row0 = blockIdx.x * kKeysPerCta;
    if (threadIdx.x == 0)
        asm volatile("cp.async.bulk.prefetch.L2.global [%0], %1;" :: "l"(k_cache + (size_t)row0 * kD), "n"(3 * kSlotBytes) : "memory");

    extern __shared__ uint8_t smem_raw[];
    const uint32_t sbase = (smem_u32(smem_raw) + 1023) & ~1023u;
    const uint32_t aux = sbase + kNS * kSlotBytes;
    const uint32_t full = aux + kOffBar, empty = full + kNS * 8;

    uint32_t t0 = 0;
    if (threadIdx.x == kNC) {
        t0 = timer_ns();
#pragma unroll
        for (int s = 0; s < kNS; s++) mbar_init(full + s * 8, 1);
        asm volatile("fence.mbarrier_init.release.cluster;" ::: "memory");
#pragma unroll
        for (int i = 0; i < 3; i++) {
            mbar_expect_tx(full + i * 8, kSlotBytes);
            tma_tile(sbase + i * kSlotBytes, &tmK, row0 + i * kTile, full + i * 8);
        }
#pragma unroll
        for (int s = 0; s < kNS; s++) mbar_init(empty + s * 8, kNW);
    }
    const int warp = threadIdx.x >> 5, lane = threadIdx.x & 31;
    const int pair = blockIdx.x >> 2, split = blockIdx.x & 3;

    if (warp == kNW) {
        __syncwarp();
        bar_arrive<1, kThreads>();
        if (lane == 0) {
#pragma unroll 1
            for (int i = 3; i < kNL; i++) {
                const int s = i % kNS;
                mbar_wait(empty + s * 8, ((i / kNS) & 1) ^ 1);
                if (i >= kFreeLoads) {
                    const uint32_t due = (uint32_t)(pace_off_ns + (((i - kFreeLoads) * pace_tau_q8) >> 8));
                    const int j = i - kMinInflight;
                    while (timer_ns() - t0 < due && !mbar_test(full + (j % kNS) * 8, (j / kNS) & 1)) { }
                }
                mbar_expect_tx(full + s * 8, kSlotBytes);
                if (i < kNL - kFin) {
                    const int j = i - kLead;
                    const bool is_k = i < kLead || (i < kNL - kLead && !(j & 1));
                    const int tile = i < kLead ? i : i >= kNL - kLead ? i - kNT : is_k ? kLead + (j >> 1) : (j >> 1);
                    tma_tile(sbase + s * kSlotBytes, is_k ? &tmK : &tmV, row0 + tile * kTile, full + s * 8);
                    if (i == kNL - 2 * kFin) asm volatile("prefetch.tensormap [%0];" :: "l"(&tmStrip) : "memory");
                } else {
                    tma_strip(sbase + s * kSlotBytes, &tmStrip, split * 32,
                              pair * kC + (i - (kNL - kFin) + 1) * kKeysPerCta - kFin * kTile, full + s * 8);
                }
            }
        }
        return;
    }

    const int tid = threadIdx.x;
    const int g = lane >> 2, t = lane & 3;

    uint32_t qa[8][2];
    {
        const uint32_t* qp = reinterpret_cast<const uint32_t*>(q + (size_t)(pair * 2 + (g & 1)) * kD);
#pragma unroll
        for (int j = 0; j < 8; j++) { qa[j][0] = __ldg(qp + j * 8 + t); qa[j][1] = __ldg(qp + j * 8 + 4 + t); }
    }
    uint64_t* boxes = inboxes + (size_t)pair * kSplit * kBoxWords;
    __nv_bfloat16* op = out + (size_t)(pair * 2 + (t & 1)) * kD + split * 32 + (warp & 1) * 16 + (t >> 1) * 8 + g;
    asm volatile("" : "+l"(boxes), "+l"(op));
    uint64_t* inbox = boxes + split * kBoxWords;
    auto outbox = [&](int r) { return boxes + r * kBoxWords + ((split - r - 1) & 3) * kSecWords; };

    float acc[8][4];
    float m = -INFINITY, l = 0.f;
#pragma unroll
    for (int j = 0; j < 8; j++) { acc[j][0] = acc[j][1] = acc[j][2] = acc[j][3] = 0.f; }
    if (split == kSplit - 1 && warp == 0) {
        const uint32_t* kp = reinterpret_cast<const uint32_t*>(k_tree + (size_t)pair * kD);
        const __nv_bfloat16* vp = v_tree + (size_t)pair * kD;
        float s4[4] = {0.f, 0.f, 0.f, 0.f};
#pragma unroll
        for (int j = 0; j < 8; j++) {
            mma16816(s4, qa[j][0], 0u, qa[j][1], 0u, __ldg(kp + j * 8 + t), __ldg(kp + j * 8 + 4 + t));
            acc[j][0] = acc[j][1] = __bfloat162float(vp[j * 16 + g]);
            acc[j][2] = acc[j][3] = __bfloat162float(vp[j * 16 + 8 + g]);
        }
        const float keep = __bfloat162float(mask[pair / kHkv]);
        m = bf_round(bf_lo(scale_scores(s4[0], s4[1])) + bf_round(bf_round(1.0f - keep) * -1000000000.0f));
        l = (t == 0) ? 1.f : 0.f;
    }

    const int r7 = lane & 7, mi = lane >> 3;
    const uint32_t ka0 = sbase + (uint32_t)(warp * 16 + r7) * 128 + ((mi ^ r7) << 4);
    const uint32_t ka1 = sbase + (uint32_t)(warp * 16 + r7) * 128 + (((4 + mi) ^ r7) << 4);
    uint32_t va[4];
#pragma unroll
    for (int jj = 0; jj < 4; jj++)
        va[jj] = sbase + (uint32_t)(warp * 16 + (mi >> 1) * 8 + r7) * 128 + (((jj * 2 + (mi & 1)) ^ r7) << 4);

    bar_sync<1, kThreads>();

    auto release = [&](int s) {
        __syncwarp();
        if (lane == 0) mbar_arrive(empty + s * 8);
    };
    auto probs = [&](uint32_t& s01, uint32_t& s23) {
        const float p0 = expdiff(bf_lo(s01), m), p1 = expdiff(bf_hi(s01), m);
        const float p2 = expdiff(bf_lo(s23), m), p3 = expdiff(bf_hi(s23), m);
        l += (p0 + p1) + (p2 + p3);
        s01 = pack_bf16(p0, p1); s23 = pack_bf16(p2, p3);
    };
    auto pv = [&](int s, int parity, uint32_t b0, uint32_t b1) {
        uint32_t a[4];
#pragma unroll
        for (int jj = 0; jj < 4; jj++) a[jj] = va[jj] + s * kSlotBytes;
        asm volatile("" : "+r"(a[0]), "+r"(a[1]), "+r"(a[2]), "+r"(a[3]));
        mbar_wait(full + s * 8, parity);
#pragma unroll
        for (int j = 0; j < 8; j++) {
            uint32_t r[4];
            ldsm4t(r, a[j & 3] + (j >> 2) * kHalf);
            mma16816(acc[j], r[0], r[1], r[2], r[3], b0, b1);
        }
    };

    uint32_t fifo[kLead + 1][2];
#pragma unroll
    for (int x = 0; x <= kLead; x++) fifo[x][0] = fifo[x][1] = 0u;
    int s = 0, ph = 0;
#pragma unroll 1
    for (int n = -kLead;; n++) {
#pragma unroll
        for (int x = 0; x < kLead; x++) { fifo[x][0] = fifo[x + 1][0]; fifo[x][1] = fifo[x + 1][1]; }
        {
            uint32_t a0 = ka0 + s * kSlotBytes, a1 = ka1 + s * kSlotBytes;
            asm volatile("" : "+r"(a0), "+r"(a1));
            mbar_wait(full + s * 8, ph);
            float sc[2][2][4];
#pragma unroll
            for (int u = 0; u < 2; u++)
#pragma unroll
                for (int c = 0; c < 2; c++) sc[u][c][0] = sc[u][c][1] = sc[u][c][2] = sc[u][c][3] = 0.f;
#pragma unroll
            for (int qd = 0; qd < 4; qd++) {
#pragma unroll
                for (int u = 0; u < 2; u++) {
                    uint32_t r[4];
                    ldsm4(r, ((qd & 1) ? a1 : a0) + u * 1024 + (qd >> 1) * kHalf);
                    mma16816(sc[u][0], qa[2 * qd][0], 0u, qa[2 * qd][1], 0u, r[0], r[1]);
                    mma16816(sc[u][1], qa[2 * qd + 1][0], 0u, qa[2 * qd + 1][1], 0u, r[2], r[3]);
                }
            }
            release(s);
            if (++s == kNS) { s = 0; ph ^= 1; }
            const uint32_t s01 = scale_scores(sc[0][0][0] + sc[0][1][0], sc[0][0][1] + sc[0][1][1]);
            const uint32_t s23 = scale_scores(sc[1][0][0] + sc[1][1][0], sc[1][0][1] + sc[1][1][1]);
            fifo[kLead][0] = s01; fifo[kLead][1] = s23;
            float mx = fmaxf(fmaxf(bf_lo(s01), bf_hi(s01)), fmaxf(bf_lo(s23), bf_hi(s23)));
            mx = fmaxf(mx, __shfl_xor_sync(0xffffffffu, mx, 1));
            mx = fmaxf(mx, __shfl_xor_sync(0xffffffffu, mx, 2));
            if (__any_sync(0xffffffffu, mx > m)) {
                const float mn = fmaxf(m, mx);
                const float f = expdiff(m, mn), fo = __shfl_xor_sync(0xffffffffu, f, 4);
                const float f0 = (g & 1) ? fo : f, f1 = (g & 1) ? f : fo;
                m = mn; l *= f;
#pragma unroll
                for (int j = 0; j < 8; j++) { acc[j][0] *= f0; acc[j][1] *= f1; acc[j][2] *= f0; acc[j][3] *= f1; }
            }
        }
        if (n == kNT - kLead - 1) break;
        if (n >= 0) {
            probs(fifo[0][0], fifo[0][1]);
            pv(s, ph, fifo[0][0], fifo[0][1]);
            release(s);
            if (++s == kNS) { s = 0; ph ^= 1; }
        }
    }

    float f0[kNW], f1[kNW], sM0 = -INFINITY, sM1 = -INFINITY, sL0 = 0.f, sL1 = 0.f;
    {
        uint64_t* ob = outbox((split + 1 + (g >> 1)) & 3);
#pragma unroll
        for (int u = 0; u < kFin; u++) {
            const int wd = (u * kNW + warp) * 8 + (g & 1) * 4 + t;
            if ((g >> 1) < 3) st_word(ob + kSecScore + wd, make_word(fifo[kEarly + u][0], fifo[kEarly + u][1]));
            else sts2(aux + kOffP + split * 1024 + wd * 8, fifo[kEarly + u][0], fifo[kEarly + u][1]);
        }
#pragma unroll
        for (int x = 0; x <= kLead; x++) probs(fifo[x][0], fifo[x][1]);
        float lr = l + __shfl_xor_sync(0xffffffffu, l, 1);
        lr += __shfl_xor_sync(0xffffffffu, lr, 2);
        if (t == 0 && g < 2) sts2(aux + kOffMl + warp * 16 + g * 8, __float_as_uint(m), __float_as_uint(lr));
        bar_sync<2, kNC>();
        float mm[kNW][4];
#pragma unroll
        for (int w = 0; w < kNW; w++) {
            lds4(mm[w], aux + kOffMl + w * 16);
            sM0 = fmaxf(sM0, mm[w][0]); sM1 = fmaxf(sM1, mm[w][2]);
        }
#pragma unroll
        for (int w = 0; w < kNW; w++) {
            f0[w] = expdiff(mm[w][0], sM0); f1[w] = expdiff(mm[w][2], sM1);
            sL0 = fmaf(f0[w], mm[w][1], sL0); sL1 = fmaf(f1[w], mm[w][3], sL1);
        }
        if (warp == 0 && (g >> 1) < 3 && !(g & 1))
            st_word(ob + kSecStat + t, (t & 1) ? make_word(sL0, sL1) : make_word(sM0, sM1));
    }

    uint64_t sw[3] = {0ull, 0ull, 0ull}, wm[3] = {0ull, 0ull, 0ull}, wl[3] = {0ull, 0ull, 0ull};
#pragma unroll
    for (int x = 0; x < kEarly; x++) {
        const int i = kNL - 1 - kLead + x;
        if (x == kEarly - 3) {
#pragma unroll
            for (int y = 0; y < 3; y++) {
                ld_word_if(sw[y], inbox + y * kSecWords + kSecScore + tid, true);
                ld_word2_if(wm[y], wl[y], inbox + y * kSecWords + kSecStat, true);
            }
        }
        pv(i % kNS, (i / kNS) & 1, fifo[x][0], fifo[x][1]);
        if (i + kNS < kNL) release(i % kNS);
    }

    if (t == 0) {
#pragma unroll
        for (int j = 0; j < 8; j++) sts4(aux + kOffAcc + warp * 1024 + j * 128 + g * 16, acc[j]);
    }
    bar_sync<2, kNC>();
    if (warp != split) {
        float o0 = 0.f, o1 = 0.f;
#pragma unroll
        for (int w = 0; w < kNW; w++) {
            uint32_t a0, a1;
            lds2(a0, a1, aux + kOffAcc + w * 1024 + (tid >> 4) * 128 + (tid & 7) * 16 + ((tid >> 3) & 1) * 8);
            o0 = fmaf(f0[w], __uint_as_float(a0), o0); o1 = fmaf(f1[w], __uint_as_float(a1), o1);
        }
        st_word(outbox(warp) + kSecOut + lane, make_word(o0 * rcp(sL0), o1 * rcp(sL1)));
    }

#pragma unroll 1
    for (int it = 0;; it++) {
        bool ms[3], mt[3];
#pragma unroll
        for (int y = 0; y < 3; y++) { ms[y] = missing(sw[y]); mt[y] = missing(wm[y]) || missing(wl[y]); }
        if (!(ms[0] || ms[1] || ms[2] || mt[0] || mt[1] || mt[2])) break;
        if (it > (1 << 22)) __trap();
#pragma unroll
        for (int y = 0; y < 3; y++) {
            ld_word_if(sw[y], inbox + y * kSecWords + kSecScore + tid, ms[y]);
            ld_word2_if(wm[y], wl[y], inbox + y * kSecWords + kSecStat, mt[y]);
        }
    }
    __syncwarp();
    float wy[3];
    {
        const float M0 = fmaxf(fmaxf(sM0, word_lo(wm[0])), fmaxf(word_lo(wm[1]), word_lo(wm[2])));
        const float M1 = fmaxf(fmaxf(sM1, word_hi(wm[0])), fmaxf(word_hi(wm[1]), word_hi(wm[2])));
        float c0[3], c1[3];
#pragma unroll
        for (int y = 0; y < 3; y++) {
            c0[y] = expdiff(word_lo(wm[y]), M0) * word_lo(wl[y]);
            c1[y] = expdiff(word_hi(wm[y]), M1) * word_hi(wl[y]);
        }
        const float e0 = expdiff(sM0, M0), e1 = expdiff(sM1, M1);
        const float r0 = rcp((c0[0] + c0[2]) + (c0[1] + e0 * sL0)), r1 = rcp((c1[0] + c1[2]) + (c1[1] + e1 * sL1));
#pragma unroll
        for (int y = 0; y < 3; y++) wy[y] = (t & 1) ? c1[y] * r1 : c0[y] * r0;
#pragma unroll
        for (int w = 0; w < kNW; w++) { f0[w] *= e0 * r0; f1[w] *= e1 * r1; }
        const float Mh = (tid & 4) ? M1 : M0, rh = (tid & 4) ? r1 : r0;
#pragma unroll
        for (int y = 0; y < kSplit; y++) {
            const uint32_t pa = aux + kOffP + ((split + 1 + y) & 3) * 1024 + tid * 8;
            uint32_t s01, s23;
            if (y < 3) {
                s01 = (uint32_t)sw[y]; s23 = (uint32_t)(sw[y] >> 32);
                st_word(inbox + y * kSecWords + kSecScore + tid, 0ull);
            } else {
                lds2(s01, s23, pa);
            }
            sts2(pa, pack_bf16(expdiff(bf_lo(s01), Mh) * rh, expdiff(bf_hi(s01), Mh) * rh),
                     pack_bf16(expdiff(bf_lo(s23), Mh) * rh, expdiff(bf_hi(s23), Mh) * rh));
        }
    }
    bar_sync<2, kNC>();
    if (warp == 3 && lane < 12) st_word(inbox + (lane >> 2) * kSecWords + kSecStat + (lane & 3), 0ull);
    if (warp >= 2) return;

    float c[4][4];
#pragma unroll
    for (int k = 0; k < 4; k++) c[k][0] = c[k][1] = c[k][2] = c[k][3] = 0.f;
#pragma unroll
    for (int w = 0; w < kNW; w++) {
        float v[4];
        lds4(v, aux + kOffAcc + w * 1024 + (split * 2 + warp) * 128 + g * 16);
        c[0][0] = fmaf(f0[w], v[0], c[0][0]); c[0][1] = fmaf(f1[w], v[1], c[0][1]);
        c[0][2] = fmaf(f0[w], v[2], c[0][2]); c[0][3] = fmaf(f1[w], v[3], c[0][3]);
    }
    uint32_t la = sbase + (uint32_t)((mi >> 1) * 8 + r7) * 64 + (((warp * 2 + (mi & 1)) ^ (r7 >> 1)) << 4);
    uint64_t* oin = inbox + kSecOut + warp * 16 + (t >> 1) * 8 + g;
    uint64_t ow[3] = {0ull, 0ull, 0ull};
    asm volatile("" : "+r"(la), "+l"(oin), "+l"(ow[0]), "+l"(ow[1]), "+l"(ow[2]));
#pragma unroll
    for (int x = 0; x < kSplit; x++) {
        const int i = kNL - kFin + x;
        uint32_t pb[16][2];
#pragma unroll
        for (int k = 0; k < 16; k++) lds2(pb[k][0], pb[k][1], aux + kOffP + x * 1024 + k * 64 + (g & 1) * 32 + t * 8);
        if (x == kSplit - 1) {
#pragma unroll
            for (int y = 0; y < 3; y++) ld_word_if(ow[y], oin + y * kSecWords, true);
        }
        mbar_wait(full + (i % kNS) * 8, (i / kNS) & 1);
#pragma unroll
        for (int k = 0; k < 16; k++) {
            uint32_t r[4];
            ldsm4t(r, la + (i % kNS) * kSlotBytes + k * 1024);
            mma16816(c[k & 3], r[0], r[1], r[2], r[3], pb[k][0], pb[k][1]);
        }
    }
    const uint32_t t1 = t & 1, t2 = t & 2;
    const float o = (sel(t2, sel(t1, c[0][3], c[0][2]), sel(t1, c[0][1], c[0][0])) + sel(t2, sel(t1, c[1][3], c[1][2]), sel(t1, c[1][1], c[1][0])))
                  + (sel(t2, sel(t1, c[2][3], c[2][2]), sel(t1, c[2][1], c[2][0])) + sel(t2, sel(t1, c[3][3], c[3][2]), sel(t1, c[3][1], c[3][0])));
#pragma unroll 1
    for (int it = 0; missing(ow[0]) || missing(ow[1]) || missing(ow[2]); it++) {
        if (it > (1 << 22)) __trap();
#pragma unroll
        for (int y = 0; y < 3; y++) ld_word_if(ow[y], oin + y * kSecWords, missing(ow[y]));
    }
    st_bf16(op, fmaf(wy[0], sel(t1, word_hi(ow[0]), word_lo(ow[0])), o)
              + fmaf(wy[1], sel(t1, word_hi(ow[1]), word_lo(ow[1])), wy[2] * sel(t1, word_hi(ow[2]), word_lo(ow[2]))));
    __syncwarp();
    if (!t1) {
#pragma unroll
        for (int y = 0; y < 3; y++) st_word(oin + y * kSecWords, 0ull);
    }
}

typedef CUresult (*EncodeTiledFn)(CUtensorMap*, CUtensorMapDataType, cuuint32_t, void*, const cuuint64_t*, const cuuint64_t*,
                                  const cuuint32_t*, const cuuint32_t*, CUtensorMapInterleave, CUtensorMapSwizzle,
                                  CUtensorMapL2promotion, CUtensorMapFloatOOBfill);

CUtensorMap make_tile_map(EncodeTiledFn encode, void* base) {
    CUtensorMap m;
    const cuuint64_t dims[3] = {64, (cuuint64_t)kPairs * kC, 2};
    const cuuint64_t strides[2] = {256, 128};
    const cuuint32_t box[3] = {64, (cuuint32_t)kTile, 2};
    const cuuint32_t elem[3] = {1, 1, 1};
    encode(&m, CU_TENSOR_MAP_DATA_TYPE_BFLOAT16, 3, base, dims, strides, box, elem, CU_TENSOR_MAP_INTERLEAVE_NONE,
           CU_TENSOR_MAP_SWIZZLE_128B, CU_TENSOR_MAP_L2_PROMOTION_L2_256B, CU_TENSOR_MAP_FLOAT_OOB_FILL_NONE);
    return m;
}

CUtensorMap make_strip_map(EncodeTiledFn encode, void* base) {
    CUtensorMap m;
    const cuuint64_t dims[2] = {(cuuint64_t)kD, (cuuint64_t)kPairs * kC};
    const cuuint64_t strides[1] = {256};
    const cuuint32_t box[2] = {32, (cuuint32_t)(kFin * kTile)};
    const cuuint32_t elem[2] = {1, 1};
    encode(&m, CU_TENSOR_MAP_DATA_TYPE_BFLOAT16, 2, base, dims, strides, box, elem, CU_TENSOR_MAP_INTERLEAVE_NONE,
           CU_TENSOR_MAP_SWIZZLE_64B, CU_TENSOR_MAP_L2_PROMOTION_L2_256B, CU_TENSOR_MAP_FLOAT_OOB_FILL_NONE);
    return m;
}

}

extern "C" void kernel_launch(void* const* d_in, const int* in_sizes, int n_in, void* d_out, int out_size) {
    (void)in_sizes; (void)n_in; (void)out_size;
    static EncodeTiledFn encode = nullptr;
    static void* inboxes = nullptr;
    static int pace_off_ns = 0, pace_tau_q8 = 0;
    if (!encode) {
        cudaDriverEntryPointQueryResult qr;
        cudaGetDriverEntryPoint("cuTensorMapEncodeTiled", (void**)&encode, cudaEnableDefault, &qr);
        cudaFuncSetAttribute(tree_attn_decode_kernel, cudaFuncAttributeMaxDynamicSharedMemorySize, kSmemBytes);
        cudaGetSymbolAddress(&inboxes, g_inbox);
        int dev = 0, mem_khz = 0, bus_bits = 0;
        cudaGetDevice(&dev);
        cudaDeviceGetAttribute(&mem_khz, cudaDevAttrMemoryClockRate, dev);
        cudaDeviceGetAttribute(&bus_bits, cudaDevAttrGlobalMemoryBusWidth, dev);
        const double bytes_per_ns = 2.0 * mem_khz * 1e-6 * bus_bits / 8.0;
        if (bytes_per_ns > 0.0) {
            const double tau = (double)kPairs * kSplit * kSlotBytes / (0.9595 * bytes_per_ns);
            pace_tau_q8 = (int)(tau * 256.0);
            pace_off_ns = (int)(2.0 * tau);
        }
    }
    const CUtensorMap tmK = make_tile_map(encode, d_in[1]);
    const CUtensorMap tmV = make_tile_map(encode, d_in[2]);
    const CUtensorMap tmStrip = make_strip_map(encode, d_in[2]);
    tree_attn_decode_kernel<<<kPairs * kSplit, kThreads, kSmemBytes>>>(
        tmK, tmV, tmStrip, (const __nv_bfloat16*)d_in[0], (const __nv_bfloat16*)d_in[1], (const __nv_bfloat16*)d_in[3],
        (const __nv_bfloat16*)d_in[4], (const __nv_bfloat16*)d_in[5], (__nv_bfloat16*)d_out, (uint64_t*)inboxes,
        pace_off_ns, pace_tau_q8);
}
```

```cpp
#include <cuda_runtime.h>
#include <cuda_bf16.h>
#include <cuda.h>
#include <stdint.h>

namespace {

constexpr int kB = 2, kHkv = 16, kC = 8192, kD = 128;
constexpr int kPairs = kB * kHkv;
constexpr int kSplit = 4;
constexpr int kKeysPerCta = kC / kSplit;
constexpr int kTile = 64;
constexpr int kNW = kTile / 16;
constexpr int kNC = kNW * 32;
constexpr int kThreads = kNC + 32;
constexpr int kNS = 8;
constexpr int kNT = kKeysPerCta / kTile;
constexpr int kNL = 2 * kNT;
constexpr int kLead = 10;
constexpr int kFin = 4;
constexpr int kEarly = kLead + 1 - kFin;
constexpr int kSlotBytes = kTile * kD * 2;
constexpr uint32_t kHalf = kTile * 128;
constexpr int kFreeLoads = 4;
constexpr int kMinInflight = 2;
constexpr int kFar = 1 << 29;
constexpr float kScale = 0.08838834764831845f;
constexpr float kLog2e = 1.4426950408889634f;
constexpr uint32_t kOffAcc = 0;
constexpr uint32_t kOffMl = kOffAcc + kNW * 1024;
constexpr uint32_t kOffP = kOffMl + kNW * 16;
constexpr uint32_t kOffPace = kOffP + kSplit * 1024;
constexpr uint32_t kOffBar = kOffPace + 16;
constexpr int kSmemBytes = 1024   + kNS * kSlotBytes + kOffBar + 2 * kNS * 8;
static_assert(kNC == kD && kSplit == 4 && kNW == 4 && kFin == 4, "layout assumptions");
static_assert(kLead >= 3 && kEarly >= 3 && kFin <= kNS, "load order assumptions");

constexpr int kSecScore = 0;
constexpr int kSecStat = 128;
constexpr int kSecOut = 144;
constexpr int kSecWords = 176;
constexpr int kBoxWords = 3 * kSecWords;
__device__ __align__(128) uint64_t g_inbox[kPairs * kSplit * kBoxWords];

__device__ __forceinline__ uint32_t smem_u32(const void* p) { return (uint32_t)__cvta_generic_to_shared(p); }
__device__ __forceinline__ uint32_t timer_ns() { uint32_t t; asm volatile("mov.u32 %0, %globaltimer_lo;" : "=r"(t)); return t; }
__device__ __forceinline__ void mbar_init(uint32_t bar, uint32_t cnt) {
    asm volatile("mbarrier.init.shared::cta.b64 [%0], %1;" :: "r"(bar), "r"(cnt) : "memory");
}
__device__ __forceinline__ void mbar_expect_tx(uint32_t bar, uint32_t bytes) {
    asm volatile("mbarrier.arrive.expect_tx.shared::cta.b64 _, [%0], %1;" :: "r"(bar), "r"(bytes) : "memory");
}
__device__ __forceinline__ void mbar_arrive(uint32_t bar) {
    asm volatile("mbarrier.arrive.shared::cta.b64 _, [%0];" :: "r"(bar) : "memory");
}
__device__ __forceinline__ void mbar_wait(uint32_t bar, uint32_t parity) {
    asm volatile(
        "{\n"
        ".reg .pred p, q;\n"
        ".reg .u32 c;\n"
        "mov.u32 c, 0;\n"
        "LAB_WAIT:\n"
        "mbarrier.try_wait.parity.shared::cta.b64 p, [%0], %1;\n"
        "@p bra LAB_DONE;\n"
        "add.u32 c, c, 1;\n"
        "setp.lt.u32 q, c, 0x1000000;\n"
        "@q bra LAB_WAIT;\n"
        "trap;\n"
        "LAB_DONE:\n"
        "}\n" :: "r"(bar), "r"(parity) : "memory");
}
template <int ID, int N> __device__ __forceinline__ void bar_sync() { asm volatile("bar.sync %0, %1;" :: "n"(ID), "n"(N) : "memory"); }
template <int ID, int N> __device__ __forceinline__ void bar_arrive() { asm volatile("bar.arrive %0, %1;" :: "n"(ID), "n"(N) : "memory"); }
__device__ __forceinline__ void tma_tile(uint32_t dst, const CUtensorMap* tm, int row, uint32_t bar) {
    asm volatile("cp.async.bulk.tensor.3d.shared::cluster.global.mbarrier::complete_tx::bytes [%0], [%1, {%3, %4, %3}], [%2];"
                 :: "r"(dst), "l"(tm), "r"(bar), "r"(0), "r"(row) : "memory");
}
__device__ __forceinline__ void tma_strip(uint32_t dst, const CUtensorMap* tm, int col, int row, uint32_t bar) {
    asm volatile("cp.async.bulk.tensor.2d.shared::cluster.global.mbarrier::complete_tx::bytes [%0], [%1, {%3, %4}], [%2];"
                 :: "r"(dst), "l"(tm), "r"(bar), "r"(col), "r"(row) : "memory");
}
__device__ __forceinline__ void ldsm4(uint32_t (&r)[4], uint32_t addr) {
    asm volatile("ldmatrix.sync.aligned.m8n8.x4.shared.b16 {%0,%1,%2,%3}, [%4];"
                 : "=r"(r[0]), "=r"(r[1]), "=r"(r[2]), "=r"(r[3]) : "r"(addr));
}
__device__ __forceinline__ void ldsm4t(uint32_t (&r)[4], uint32_t addr) {
    asm volatile("ldmatrix.sync.aligned.m8n8.x4.trans.shared.b16 {%0,%1,%2,%3}, [%4];"
                 : "=r"(r[0]), "=r"(r[1]), "=r"(r[2]), "=r"(r[3]) : "r"(addr));
}
__device__ __forceinline__ void mma16816(float (&d)[4], uint32_t a0, uint32_t a1, uint32_t a2, uint32_t a3, uint32_t b0, uint32_t b1) {
    asm volatile("mma.sync.aligned.m16n8k16.row.col.f32.bf16.bf16.f32 {%0,%1,%2,%3}, {%4,%5,%6,%7}, {%8,%9}, {%0,%1,%2,%3};"
                 : "+f"(d[0]), "+f"(d[1]), "+f"(d[2]), "+f"(d[3]) : "r"(a0), "r"(a1), "r"(a2), "r"(a3), "r"(b0), "r"(b1));
}
__device__ __forceinline__ void sts2(uint32_t a, uint32_t x, uint32_t y) {
    asm volatile("st.shared.v2.b32 [%0], {%1,%2};" :: "r"(a), "r"(x), "r"(y) : "memory");
}
__device__ __forceinline__ void lds2(uint32_t& x, uint32_t& y, uint32_t a) {
    asm volatile("ld.shared.v2.b32 {%0,%1}, [%2];" : "=r"(x), "=r"(y) : "r"(a) : "memory");
}
__device__ __forceinline__ void sts4(uint32_t a, const float (&v)[4]) {
    asm volatile("st.shared.v4.f32 [%0], {%1,%2,%3,%4};" :: "r"(a), "f"(v[0]), "f"(v[1]), "f"(v[2]), "f"(v[3]) : "memory");
}
__device__ __forceinline__ void lds4(float (&v)[4], uint32_t a) {
    asm volatile("ld.shared.v4.f32 {%0,%1,%2,%3}, [%4];" : "=f"(v[0]), "=f"(v[1]), "=f"(v[2]), "=f"(v[3]) : "r"(a) : "memory");
}
__device__ __forceinline__ float ex2(float x) { float y; asm("ex2.approx.ftz.f32 %0, %1;" : "=f"(y) : "f"(x)); return y; }
__device__ __forceinline__ float rcp(float x) { float y; asm("rcp.approx.ftz.f32 %0, %1;" : "=f"(y) : "f"(x)); return y; }
__device__ __forceinline__ float expdiff(float a, float b) { return ex2((a - b) * kLog2e); }
__device__ __forceinline__ float sel(uint32_t c, float a, float b) {
    float r; asm("{\n.reg .pred p;\nsetp.ne.u32 p, %3, 0;\nselp.f32 %0, %1, %2, p;\n}" : "=f"(r) : "f"(a), "f"(b), "r"(c)); return r;
}
__device__ __forceinline__ uint32_t pack_bf16(float lo, float hi) {
    uint32_t r; asm("cvt.rn.bf16x2.f32 %0, %1, %2;" : "=r"(r) : "f"(hi), "f"(lo)); return r;
}
__device__ __forceinline__ float bf_lo(uint32_t v) { return __uint_as_float(v << 16); }
__device__ __forceinline__ float bf_hi(uint32_t v) { return __uint_as_float(v & 0xffff0000u); }
__device__ __forceinline__ float bf_round(float x) { return __bfloat162float(__float2bfloat16(x)); }
__device__ __forceinline__ uint32_t scale_scores(float a, float b) {
    const uint32_t r = pack_bf16(a, b);
    return pack_bf16(bf_lo(r) * kScale, bf_hi(r) * kScale);
}
__device__ __forceinline__ void st_bf16(__nv_bfloat16* p, float v) {
    asm volatile("{\n.reg .b16 h;\ncvt.rn.bf16.f32 h, %1;\nst.global.b16 [%0], h;\n}" :: "l"(p), "f"(v) : "memory");
}
__device__ __forceinline__ void st_word(uint64_t* p, uint64_t v) {
    asm volatile("st.relaxed.gpu.global.b64 [%0], %1;" :: "l"(p), "l"(v) : "memory");
}
__device__ __forceinline__ void ld_word_if(uint64_t& a, const uint64_t* p, bool pred) {
    asm volatile("{\n.reg .pred p;\nsetp.ne.u32 p, %2, 0;\n@p ld.relaxed.gpu.global.b64 %0, [%1];\n}"
                 : "+l"(a) : "l"(p), "r"((uint32_t)pred) : "memory");
}
__device__ __forceinline__ void ld_word2_if(uint64_t& a, uint64_t& b, const uint64_t* p, bool pred) {
    asm volatile("{\n.reg .pred p;\nsetp.ne.u32 p, %3, 0;\n@p ld.relaxed.gpu.global.v2.b64 {%0, %1}, [%2];\n}"
                 : "+l"(a), "+l"(b) : "l"(p), "r"((uint32_t)pred) : "memory");
}
__device__ __forceinline__ uint64_t make_word(uint32_t lo, uint32_t hi) {
    if (lo == 0u) lo = 0x80000000u;
    return ((uint64_t)hi << 32) | lo;
}
__device__ __forceinline__ uint64_t make_word(float lo, float hi) { return make_word(__float_as_uint(lo), __float_as_uint(hi)); }
__device__ __forceinline__ float word_lo(uint64_t w) { return __uint_as_float((uint32_t)w); }
__device__ __forceinline__ float word_hi(uint64_t w) { return __uint_as_float((uint32_t)(w >> 32)); }
__device__ __forceinline__ bool missing(uint64_t w) { return (uint32_t)w == 0u; }

struct Pace { int off, tau_q8, limit, tau_fb_q8; };

__global__ void __launch_bounds__(kThreads, 1)
tree_attn_decode_kernel(const __grid_constant__ CUtensorMap tmK, const __grid_constant__ CUtensorMap tmV,
                        const __grid_constant__ CUtensorMap tmStrip,
                        const __nv_bfloat16* __restrict__ q, const __nv_bfloat16* __restrict__ k_cache,
                        const __nv_bfloat16* __restrict__ k_tree, const __nv_bfloat16* __restrict__ v_tree,
                        const __nv_bfloat16* __restrict__ mask, __nv_bfloat16* __restrict__ out,
                        uint64_t* __restrict__ inboxes, Pace pace)
{
    const int row0 = blockIdx.x * kKeysPerCta;
    if (threadIdx.x == 0)
        asm volatile("cp.async.bulk.prefetch.L2.global [%0], %1;" :: "l"(k_cache + (size_t)row0 * kD), "n"(3 * kSlotBytes) : "memory");

    extern __shared__ uint8_t smem_raw[];
    const uint32_t sbase = (smem_u32(smem_raw) + 1023) & ~1023u;
    const uint32_t aux = sbase + kNS * kSlotBytes;
    const uint32_t full = aux + kOffBar, empty = full + kNS * 8;

    uint32_t t0 = 0;
    if (threadIdx.x == kNC) {
        t0 = timer_ns();
#pragma unroll
        for (int s = 0; s < kNS; s++) mbar_init(full + s * 8, 1);
        asm volatile("fence.mbarrier_init.release.cluster;" ::: "memory");
#pragma unroll
        for (int i = 0; i < 3; i++) {
            mbar_expect_tx(full + i * 8, kSlotBytes);
            tma_tile(sbase + i * kSlotBytes, &tmK, row0 + i * kTile, full + i * 8);
        }
#pragma unroll
        for (int s = 0; s < kNS; s++) mbar_init(empty + s * 8, kNW);
        sts2(aux + kOffPace, t0, 0u);
        sts2(aux + kOffPace + 8, (uint32_t)-kFar, 0u);
    }
    const int warp = threadIdx.x >> 5, lane = threadIdx.x & 31;
    const int pair = blockIdx.x >> 2, split = blockIdx.x & 3;

    if (warp == kNW) {
        __syncwarp();
        bar_arrive<1, kThreads>();
        if (lane == 0) {
#pragma unroll 1
            for (int i = 3; i < kNL; i++) {
                const int s = i % kNS;
                mbar_wait(empty + s * 8, ((i / kNS) & 1) ^ 1);
                if (i >= kFreeLoads) {
                    const int due = pace.off + (((i - kFreeLoads) * pace.tau_q8) >> 8);
                    const int ahead = ((i * pace.tau_fb_q8) >> 8) - pace.limit;
                    int phase, seen;
                    do {
                        asm volatile("ld.volatile.shared.v2.s32 {%0, %1}, [%2];" : "=r"(phase), "=r"(seen) : "r"(aux + kOffPace + 8) : "memory");
                    } while ((int)(timer_ns() - t0) < max(due, phase + ahead) && seen <= i - kMinInflight);
                }
                mbar_expect_tx(full + s * 8, kSlotBytes);
                if (i < kNL - kFin) {
                    const int j = i - kLead;
                    const bool is_k = i < kLead || (i < kNL - kLead && !(j & 1));
                    const int tile = i < kLead ? i : i >= kNL - kLead ? i - kNT : is_k ? kLead + (j >> 1) : (j >> 1);
                    tma_tile(sbase + s * kSlotBytes, is_k ? &tmK : &tmV, row0 + tile * kTile, full + s * 8);
                    if (i == kNL - 2 * kFin) asm volatile("prefetch.tensormap [%0];" :: "l"(&tmStrip) : "memory");
                } else {
                    tma_strip(sbase + s * kSlotBytes, &tmStrip, split * 32,
                              pair * kC + (i - (kNL - kFin) + 1) * kKeysPerCta - kFin * kTile, full + s * 8);
                }
            }
        }
        return;
    }

    const int tid = threadIdx.x;
    const int g = lane >> 2, t = lane & 3;

    uint32_t qa[8][2];
    {
        const uint32_t* qp = reinterpret_cast<const uint32_t*>(q + (size_t)(pair * 2 + (g & 1)) * kD);
#pragma unroll
        for (int j = 0; j < 8; j++) { qa[j][0] = __ldg(qp + j * 8 + t); qa[j][1] = __ldg(qp + j * 8 + 4 + t); }
    }
    uint64_t* boxes = inboxes + (size_t)pair * kSplit * kBoxWords;
    __nv_bfloat16* op = out + (size_t)(pair * 2 + (t & 1)) * kD + split * 32 + (warp & 1) * 16 + (t >> 1) * 8 + g;
    asm volatile("" : "+l"(boxes), "+l"(op));
    uint64_t* inbox = boxes + split * kBoxWords;
    auto outbox = [&](int r) { return boxes + r * kBoxWords + ((split - r - 1) & 3) * kSecWords; };

    float acc[8][4];
    float m = -INFINITY, l = 0.f;
#pragma unroll
    for (int j = 0; j < 8; j++) { acc[j][0] = acc[j][1] = acc[j][2] = acc[j][3] = 0.f; }
    if (split == kSplit - 1 && warp == 0) {
        const uint32_t* kp = reinterpret_cast<const uint32_t*>(k_tree + (size_t)pair * kD);
        const __nv_bfloat16* vp = v_tree + (size_t)pair * kD;
        float s4[4] = {0.f, 0.f, 0.f, 0.f};
#pragma unroll
        for (int j = 0; j < 8; j++) {
            mma16816(s4, qa[j][0], 0u, qa[j][1], 0u, __ldg(kp + j * 8 + t), __ldg(kp + j * 8 + 4 + t));
            acc[j][0] = acc[j][1] = __bfloat162float(vp[j * 16 + g]);
            acc[j][2] = acc[j][3] = __bfloat162float(vp[j * 16 + 8 + g]);
        }
        const float keep = __bfloat162float(mask[pair / kHkv]);
        m = bf_round(bf_lo(scale_scores(s4[0], s4[1])) + bf_round(bf_round(1.0f - keep) * -1000000000.0f));
        l = (t == 0) ? 1.f : 0.f;
    }

    const int r7 = lane & 7, mi = lane >> 3;
    const uint32_t ka0 = sbase + (uint32_t)(warp * 16 + r7) * 128 + ((mi ^ r7) << 4);
    const uint32_t ka1 = sbase + (uint32_t)(warp * 16 + r7) * 128 + (((4 + mi) ^ r7) << 4);
    uint32_t va[4];
#pragma unroll
    for (int jj = 0; jj < 4; jj++)
        va[jj] = sbase + (uint32_t)(warp * 16 + (mi >> 1) * 8 + r7) * 128 + (((jj * 2 + (mi & 1)) ^ r7) << 4);

    bar_sync<1, kThreads>();

    uint32_t tz, unused;
    lds2(tz, unused, aux + kOffPace);
    int seen = 0, ph_cur = kFar, ph_prev = -kFar;
    auto landed = [&]() {
        if (warp == 0) {
            ph_cur = min(ph_cur, (int)(timer_ns() - tz) - ((seen * pace.tau_q8) >> 8));
            if ((++seen & 3) == 0) { ph_prev = ph_cur; ph_cur = kFar; }
            if (lane == 0)
                asm volatile("st.volatile.shared.v2.s32 [%0], {%1, %2};" :: "r"(aux + kOffPace + 8), "r"(min(ph_cur, ph_prev)), "r"(seen) : "memory");
        }
    };
    auto release = [&](int s) {
        __syncwarp();
        if (lane == 0) mbar_arrive(empty + s * 8);
    };
    auto probs = [&](uint32_t& s01, uint32_t& s23) {
        const float p0 = expdiff(bf_lo(s01), m), p1 = expdiff(bf_hi(s01), m);
        const float p2 = expdiff(bf_lo(s23), m), p3 = expdiff(bf_hi(s23), m);
        l += (p0 + p1) + (p2 + p3);
        s01 = pack_bf16(p0, p1); s23 = pack_bf16(p2, p3);
    };
    auto pv = [&](int s, int parity, uint32_t b0, uint32_t b1) {
        uint32_t a[4];
#pragma unroll
        for (int jj = 0; jj < 4; jj++) a[jj] = va[jj] + s * kSlotBytes;
        asm volatile("" : "+r"(a[0]), "+r"(a[1]), "+r"(a[2]), "+r"(a[3]));
        mbar_wait(full + s * 8, parity);
        landed();
#pragma unroll
        for (int j = 0; j < 8; j++) {
            uint32_t r[4];
            ldsm4t(r, a[j & 3] + (j >> 2) * kHalf);
            mma16816(acc[j], r[0], r[1], r[2], r[3], b0, b1);
        }
    };

    uint32_t fifo[kLead + 1][2];
#pragma unroll
    for (int x = 0; x <= kLead; x++) fifo[x][0] = fifo[x][1] = 0u;
    int s = 0, ph = 0;
#pragma unroll 1
    for (int n = -kLead;; n++) {
#pragma unroll
        for (int x = 0; x < kLead; x++) { fifo[x][0] = fifo[x + 1][0]; fifo[x][1] = fifo[x + 1][1]; }
        {
            uint32_t a0 = ka0 + s * kSlotBytes, a1 = ka1 + s * kSlotBytes;
            asm volatile("" : "+r"(a0), "+r"(a1));
            mbar_wait(full + s * 8, ph);
            landed();
            float sc[2][2][4];
#pragma unroll
            for (int u = 0; u < 2; u++)
#pragma unroll
                for (int c = 0; c < 2; c++) sc[u][c][0] = sc[u][c][1] = sc[u][c][2] = sc[u][c][3] = 0.f;
#pragma unroll
            for (int qd = 0; qd < 4; qd++) {
#pragma unroll
                for (int u = 0; u < 2; u++) {
                    uint32_t r[4];
                    ldsm4(r, ((qd & 1) ? a1 : a0) + u * 1024 + (qd >> 1) * kHalf);
                    mma16816(sc[u][0], qa[2 * qd][0], 0u, qa[2 * qd][1], 0u, r[0], r[1]);
                    mma16816(sc[u][1], qa[2 * qd + 1][0], 0u, qa[2 * qd + 1][1], 0u, r[2], r[3]);
                }
            }
            release(s);
            if (++s == kNS) { s = 0; ph ^= 1; }
            const uint32_t s01 = scale_scores(sc[0][0][0] + sc[0][1][0], sc[0][0][1] + sc[0][1][1]);
            const uint32_t s23 = scale_scores(sc[1][0][0] + sc[1][1][0], sc[1][0][1] + sc[1][1][1]);
            fifo[kLead][0] = s01; fifo[kLead][1] = s23;
            float mx = fmaxf(fmaxf(bf_lo(s01), bf_hi(s01)), fmaxf(bf_lo(s23), bf_hi(s23)));
            mx = fmaxf(mx, __shfl_xor_sync(0xffffffffu, mx, 1));
            mx = fmaxf(mx, __shfl_xor_sync(0xffffffffu, mx, 2));
            if (__any_sync(0xffffffffu, mx > m)) {
                const float mn = fmaxf(m, mx);
                const float f = expdiff(m, mn), fo = __shfl_xor_sync(0xffffffffu, f, 4);
                const float f0 = (g & 1) ? fo : f, f1 = (g & 1) ? f : fo;
                m = mn; l *= f;
#pragma unroll
                for (int j = 0; j < 8; j++) { acc[j][0] *= f0; acc[j][1] *= f1; acc[j][2] *= f0; acc[j][3] *= f1; }
            }
        }
        if (n == kNT - kLead - 1) break;
        if (n >= 0) {
            probs(fifo[0][0], fifo[0][1]);
            pv(s, ph, fifo[0][0], fifo[0][1]);
            release(s);
            if (++s == kNS) { s = 0; ph ^= 1; }
        }
    }

    float f0[kNW], f1[kNW], sM0 = -INFINITY, sM1 = -INFINITY, sL0 = 0.f, sL1 = 0.f;
    {
        uint64_t* ob = outbox((split + 1 + (g >> 1)) & 3);
#pragma unroll
        for (int u = 0; u < kFin; u++) {
            const int wd = (u * kNW + warp) * 8 + (g & 1) * 4 + t;
            if ((g >> 1) < 3) st_word(ob + kSecScore + wd, make_word(fifo[kEarly + u][0], fifo[kEarly + u][1]));
            else sts2(aux + kOffP + split * 1024 + wd * 8, fifo[kEarly + u][0], fifo[kEarly + u][1]);
        }
#pragma unroll
        for (int x = 0; x <= kLead; x++) probs(fifo[x][0], fifo[x][1]);
        float lr = l + __shfl_xor_sync(0xffffffffu, l, 1);
        lr += __shfl_xor_sync(0xffffffffu, lr, 2);
        if (t == 0 && g < 2) sts2(aux + kOffMl + warp * 16 + g * 8, __float_as_uint(m), __float_as_uint(lr));
        bar_sync<2, kNC>();
        float mm[kNW][4];
#pragma unroll
        for (int w = 0; w < kNW; w++) {
            lds4(mm[w], aux + kOffMl + w * 16);
            sM0 = fmaxf(sM0, mm[w][0]); sM1 = fmaxf(sM1, mm[w][2]);
        }
#pragma unroll
        for (int w = 0; w < kNW; w++) {
            f0[w] = expdiff(mm[w][0], sM0); f1[w] = expdiff(mm[w][2], sM1);
            sL0 = fmaf(f0[w], mm[w][1], sL0); sL1 = fmaf(f1[w], mm[w][3], sL1);
        }
        if (warp == 0 && (g >> 1) < 3 && !(g & 1))
            st_word(ob + kSecStat + t, (t & 1) ? make_word(sL0, sL1) : make_word(sM0, sM1));
    }

    uint64_t sw[3] = {0ull, 0ull, 0ull}, wm[3] = {0ull, 0ull, 0ull}, wl[3] = {0ull, 0ull, 0ull};
#pragma unroll
    for (int x = 0; x < kEarly; x++) {
        const int i = kNL - 1 - kLead + x;
        if (x == kEarly - 3) {
#pragma unroll
            for (int y = 0; y < 3; y++) {
                ld_word_if(sw[y], inbox + y * kSecWords + kSecScore + tid, true);
                ld_word2_if(wm[y], wl[y], inbox + y * kSecWords + kSecStat, true);
            }
        }
        pv(i % kNS, (i / kNS) & 1, fifo[x][0], fifo[x][1]);
        if (i + kNS < kNL) release(i % kNS);
    }

    if (t == 0) {
#pragma unroll
        for (int j = 0; j < 8; j++) sts4(aux + kOffAcc + warp * 1024 + j * 128 + g * 16, acc[j]);
    }
    bar_sync<2, kNC>();
    if (warp != split) {
        float o0 = 0.f, o1 = 0.f;
#pragma unroll
        for (int w = 0; w < kNW; w++) {
            uint32_t a0, a1;
            lds2(a0, a1, aux + kOffAcc + w * 1024 + (tid >> 4) * 128 + (tid & 7) * 16 + ((tid >> 3) & 1) * 8);
            o0 = fmaf(f0[w], __uint_as_float(a0), o0); o1 = fmaf(f1[w], __uint_as_float(a1), o1);
        }
        st_word(outbox(warp) + kSecOut + lane, make_word(o0 * rcp(sL0), o1 * rcp(sL1)));
    }

#pragma unroll 1
    for (int it = 0;; it++) {
        bool ms[3], mt[3];
#pragma unroll
        for (int y = 0; y < 3; y++) { ms[y] = missing(sw[y]); mt[y] = missing(wm[y]) || missing(wl[y]); }
        if (!(ms[0] || ms[1] || ms[2] || mt[0] || mt[1] || mt[2])) break;
        if (it > (1 << 22)) __trap();
#pragma unroll
        for (int y = 0; y < 3; y++) {
            ld_word_if(sw[y], inbox + y * kSecWords + kSecScore + tid, ms[y]);
            ld_word2_if(wm[y], wl[y], inbox + y * kSecWords + kSecStat, mt[y]);
        }
    }
    __syncwarp();
    float wy[3];
    {
        const float M0 = fmaxf(fmaxf(sM0, word_lo(wm[0])), fmaxf(word_lo(wm[1]), word_lo(wm[2])));
        const float M1 = fmaxf(fmaxf(sM1, word_hi(wm[0])), fmaxf(word_hi(wm[1]), word_hi(wm[2])));
        float c0[3], c1[3];
#pragma unroll
        for (int y = 0; y < 3; y++) {
            c0[y] = expdiff(word_lo(wm[y]), M0) * word_lo(wl[y]);
            c1[y] = expdiff(word_hi(wm[y]), M1) * word_hi(wl[y]);
        }
        const float e0 = expdiff(sM0, M0), e1 = expdiff(sM1, M1);
        const float r0 = rcp((c0[0] + c0[2]) + (c0[1] + e0 * sL0)), r1 = rcp((c1[0] + c1[2]) + (c1[1] + e1 * sL1));
#pragma unroll
        for (int y = 0; y < 3; y++) wy[y] = (t & 1) ? c1[y] * r1 : c0[y] * r0;
#pragma unroll
        for (int w = 0; w < kNW; w++) { f0[w] *= e0 * r0; f1[w] *= e1 * r1; }
        const float Mh = (tid & 4) ? M1 : M0, rh = (tid & 4) ? r1 : r0;
#pragma unroll
        for (int y = 0; y < kSplit; y++) {
            const uint32_t pa = aux + kOffP + ((split + 1 + y) & 3) * 1024 + tid * 8;
            uint32_t s01, s23;
            if (y < 3) {
                s01 = (uint32_t)sw[y]; s23 = (uint32_t)(sw[y] >> 32);
                st_word(inbox + y * kSecWords + kSecScore + tid, 0ull);
            } else {
                lds2(s01, s23, pa);
            }
            sts2(pa, pack_bf16(expdiff(bf_lo(s01), Mh) * rh, expdiff(bf_hi(s01), Mh) * rh),
                     pack_bf16(expdiff(bf_lo(s23), Mh) * rh, expdiff(bf_hi(s23), Mh) * rh));
        }
    }
    bar_sync<2, kNC>();
    if (warp == 3 && lane < 12) st_word(inbox + (lane >> 2) * kSecWords + kSecStat + (lane & 3), 0ull);
    if (warp >= 2) return;

    float c[4][4];
#pragma unroll
    for (int k = 0; k < 4; k++) c[k][0] = c[k][1] = c[k][2] = c[k][3] = 0.f;
#pragma unroll
    for (int w = 0; w < kNW; w++) {
        float v[4];
        lds4(v, aux + kOffAcc + w * 1024 + (split * 2 + warp) * 128 + g * 16);
        c[0][0] = fmaf(f0[w], v[0], c[0][0]); c[0][1] = fmaf(f1[w], v[1], c[0][1]);
        c[0][2] = fmaf(f0[w], v[2], c[0][2]); c[0][3] = fmaf(f1[w], v[3], c[0][3]);
    }
    uint32_t la = sbase + (uint32_t)((mi >> 1) * 8 + r7) * 64 + (((warp * 2 + (mi & 1)) ^ (r7 >> 1)) << 4);
    uint64_t* oin = inbox + kSecOut + warp * 16 + (t >> 1) * 8 + g;
    uint64_t ow[3] = {0ull, 0ull, 0ull};
    asm volatile("" : "+r"(la), "+l"(oin), "+l"(ow[0]), "+l"(ow[1]), "+l"(ow[2]));
#pragma unroll
    for (int x = 0; x < kSplit; x++) {
        const int i = kNL - kFin + x;
        uint32_t pb[16][2];
#pragma unroll
        for (int k = 0; k < 16; k++) lds2(pb[k][0], pb[k][1], aux + kOffP + x * 1024 + k * 64 + (g & 1) * 32 + t * 8);
        if (x == kSplit - 1) {
#pragma unroll
            for (int y = 0; y < 3; y++) ld_word_if(ow[y], oin + y * kSecWords, true);
        }
        mbar_wait(full + (i % kNS) * 8, (i / kNS) & 1);
#pragma unroll
        for (int k = 0; k < 16; k++) {
            uint32_t r[4];
            ldsm4t(r, la + (i % kNS) * kSlotBytes + k * 1024);
            mma16816(c[k & 3], r[0], r[1], r[2], r[3], pb[k][0], pb[k][1]);
        }
    }
    const uint32_t t1 = t & 1, t2 = t & 2;
    const float o = (sel(t2, sel(t1, c[0][3], c[0][2]), sel(t1, c[0][1], c[0][0])) + sel(t2, sel(t1, c[1][3], c[1][2]), sel(t1, c[1][1], c[1][0])))
                  + (sel(t2, sel(t1, c[2][3], c[2][2]), sel(t1, c[2][1], c[2][0])) + sel(t2, sel(t1, c[3][3], c[3][2]), sel(t1, c[3][1], c[3][0])));
#pragma unroll 1
    for (int it = 0; missing(ow[0]) || missing(ow[1]) || missing(ow[2]); it++) {
        if (it > (1 << 22)) __trap();
#pragma unroll
        for (int y = 0; y < 3; y++) ld_word_if(ow[y], oin + y * kSecWords, missing(ow[y]));
    }
    st_bf16(op, fmaf(wy[0], sel(t1, word_hi(ow[0]), word_lo(ow[0])), o)
              + fmaf(wy[1], sel(t1, word_hi(ow[1]), word_lo(ow[1])), wy[2] * sel(t1, word_hi(ow[2]), word_lo(ow[2]))));
    __syncwarp();
    if (!t1) {
#pragma unroll
        for (int y = 0; y < 3; y++) st_word(oin + y * kSecWords, 0ull);
    }
}

typedef CUresult (*EncodeTiledFn)(CUtensorMap*, CUtensorMapDataType, cuuint32_t, void*, const cuuint64_t*, const cuuint64_t*,
                                  const cuuint32_t*, const cuuint32_t*, CUtensorMapInterleave, CUtensorMapSwizzle,
                                  CUtensorMapL2promotion, CUtensorMapFloatOOBfill);

CUtensorMap make_tile_map(EncodeTiledFn encode, void* base) {
    CUtensorMap m;
    const cuuint64_t dims[3] = {64, (cuuint64_t)kPairs * kC, 2};
    const cuuint64_t strides[2] = {256, 128};
    const cuuint32_t box[3] = {64, (cuuint32_t)kTile, 2};
    const cuuint32_t elem[3] = {1, 1, 1};
    encode(&m, CU_TENSOR_MAP_DATA_TYPE_BFLOAT16, 3, base, dims, strides, box, elem, CU_TENSOR_MAP_INTERLEAVE_NONE,
           CU_TENSOR_MAP_SWIZZLE_128B, CU_TENSOR_MAP_L2_PROMOTION_L2_256B, CU_TENSOR_MAP_FLOAT_OOB_FILL_NONE);
    return m;
}

CUtensorMap make_strip_map(EncodeTiledFn encode, void* base) {
    CUtensorMap m;
    const cuuint64_t dims[2] = {(cuuint64_t)kD, (cuuint64_t)kPairs * kC};
    const cuuint64_t strides[1] = {256};
    const cuuint32_t box[2] = {32, (cuuint32_t)(kFin * kTile)};
    const cuuint32_t elem[2] = {1, 1};
    encode(&m, CU_TENSOR_MAP_DATA_TYPE_BFLOAT16, 2, base, dims, strides, box, elem, CU_TENSOR_MAP_INTERLEAVE_NONE,
           CU_TENSOR_MAP_SWIZZLE_64B, CU_TENSOR_MAP_L2_PROMOTION_L2_256B, CU_TENSOR_MAP_FLOAT_OOB_FILL_NONE);
    return m;
}

}

extern "C" void kernel_launch(void* const* d_in, const int* in_sizes, int n_in, void* d_out, int out_size) {
    (void)in_sizes; (void)n_in; (void)out_size;
    static EncodeTiledFn encode = nullptr;
    static void* inboxes = nullptr;
    static Pace pace = {0, 0, 0, 0};
    if (!encode) {
        cudaDriverEntryPointQueryResult qr;
        cudaGetDriverEntryPoint("cuTensorMapEncodeTiled", (void**)&encode, cudaEnableDefault, &qr);
        cudaFuncSetAttribute(tree_attn_decode_kernel, cudaFuncAttributeMaxDynamicSharedMemorySize, kSmemBytes);
        cudaGetSymbolAddress(&inboxes, g_inbox);
        int dev = 0, mem_khz = 0, bus_bits = 0;
        cudaGetDevice(&dev);
        cudaDeviceGetAttribute(&mem_khz, cudaDevAttrMemoryClockRate, dev);
        cudaDeviceGetAttribute(&bus_bits, cudaDevAttrGlobalMemoryBusWidth, dev);
        const double bytes_per_ns = 2.0 * mem_khz * 1e-6 * bus_bits / 8.0;
        if (bytes_per_ns > 0.0) {
            const double tau = (double)kPairs * kSplit * kSlotBytes / (0.9595 * bytes_per_ns);
            pace = {(int)(2.0 * tau), (int)(tau * 256.0), (int)(4.14 * tau), (int)(1.02 * tau * 256.0)};
        }
    }
    const CUtensorMap tmK = make_tile_map(encode, d_in[1]);
    const CUtensorMap tmV = make_tile_map(encode, d_in[2]);
    const CUtensorMap tmStrip = make_strip_map(encode, d_in[2]);
    tree_attn_decode_kernel<<<kPairs * kSplit, kThreads, kSmemBytes>>>(
        tmK, tmV, tmStrip, (const __nv_bfloat16*)d_in[0], (const __nv_bfloat16*)d_in[1], (const __nv_bfloat16*)d_in[3],
        (const __nv_bfloat16*)d_in[4], (const __nv_bfloat16*)d_in[5], (__nv_bfloat16*)d_out, (uint64_t*)inboxes, pace);
}
```

```cpp
#include <cuda_runtime.h>
#include <cuda_bf16.h>
#include <cuda.h>
#include <stdint.h>

namespace {

constexpr int kB = 2, kHkv = 16, kC = 8192, kD = 128;
constexpr int kPairs = kB * kHkv;
constexpr int kSplit = 4;
constexpr int kKeysPerCta = kC / kSplit;
constexpr int kTile = 64;
constexpr int kNW = kTile / 16;
constexpr int kNC = kNW * 32;
constexpr int kThreads = kNC + 32;
constexpr int kNS = 8;
constexpr int kNT = kKeysPerCta / kTile;
constexpr int kNL = 2 * kNT;
constexpr int kLead = 10;
constexpr int kFin = 4;
constexpr int kEarly = kLead + 1 - kFin;
constexpr int kSlotBytes = kTile * kD * 2;
constexpr uint32_t kHalf = kTile * 128;
constexpr int kFreeLoads = 4;
constexpr int kMinInflight = 2;
constexpr int kFar = 1 << 29;
constexpr float kScale = 0.08838834764831845f;
constexpr float kLog2e = 1.4426950408889634f;
constexpr uint32_t kOffAcc = 0;
constexpr uint32_t kOffMl = kOffAcc + kNW * 1024;
constexpr uint32_t kOffP = kOffMl + kNW * 16;
constexpr uint32_t kOffPace = kOffP + kSplit * 1024;
constexpr uint32_t kOffBar = kOffPace + 16;
constexpr int kSmemBytes = 1024   + kNS * kSlotBytes + kOffBar + 2 * kNS * 8;
static_assert(kNC == kD && kSplit == 4 && kNW == 4 && kFin == 4, "layout assumptions");
static_assert(kLead >= 3 && kEarly >= 3 && kFin <= kNS, "load order assumptions");

constexpr int kSecScore = 0;
constexpr int kSecStat = 128;
constexpr int kSecOut = 144;
constexpr int kSecWords = 176;
constexpr int kBoxWords = 3 * kSecWords;
__device__ __align__(128) uint64_t g_inbox[kPairs * kSplit * kBoxWords];

__device__ __forceinline__ uint32_t smem_u32(const void* p) { return (uint32_t)__cvta_generic_to_shared(p); }
__device__ __forceinline__ uint32_t timer_ns() { uint32_t t; asm volatile("mov.u32 %0, %globaltimer_lo;" : "=r"(t)); return t; }
__device__ __forceinline__ void mbar_init(uint32_t bar, uint32_t cnt) {
    asm volatile("mbarrier.init.shared::cta.b64 [%0], %1;" :: "r"(bar), "r"(cnt) : "memory");
}
__device__ __forceinline__ void mbar_expect_tx(uint32_t bar, uint32_t bytes) {
    asm volatile("mbarrier.arrive.expect_tx.shared::cta.b64 _, [%0], %1;" :: "r"(bar), "r"(bytes) : "memory");
}
__device__ __forceinline__ void mbar_arrive(uint32_t bar) {
    asm volatile("mbarrier.arrive.shared::cta.b64 _, [%0];" :: "r"(bar) : "memory");
}
__device__ __forceinline__ void mbar_wait(uint32_t bar, uint32_t parity) {
    asm volatile(
        "{\n"
        ".reg .pred p, q;\n"
        ".reg .u32 c;\n"
        "mov.u32 c, 0;\n"
        "LAB_WAIT:\n"
        "mbarrier.try_wait.parity.shared::cta.b64 p, [%0], %1;\n"
        "@p bra LAB_DONE;\n"
        "add.u32 c, c, 1;\n"
        "setp.lt.u32 q, c, 0x1000000;\n"
        "@q bra LAB_WAIT;\n"
        "trap;\n"
        "LAB_DONE:\n"
        "}\n" :: "r"(bar), "r"(parity) : "memory");
}
template <int ID, int N> __device__ __forceinline__ void bar_sync() { asm volatile("bar.sync %0, %1;" :: "n"(ID), "n"(N) : "memory"); }
template <int ID, int N> __device__ __forceinline__ void bar_arrive() { asm volatile("bar.arrive %0, %1;" :: "n"(ID), "n"(N) : "memory"); }
__device__ __forceinline__ void tma_tile(uint32_t dst, const CUtensorMap* tm, int row, uint32_t bar) {
    asm volatile("cp.async.bulk.tensor.3d.shared::cluster.global.mbarrier::complete_tx::bytes [%0], [%1, {%3, %4, %3}], [%2];"
                 :: "r"(dst), "l"(tm), "r"(bar), "r"(0), "r"(row) : "memory");
}
__device__ __forceinline__ void tma_strip(uint32_t dst, const CUtensorMap* tm, int col, int row, uint32_t bar) {
    asm volatile("cp.async.bulk.tensor.2d.shared::cluster.global.mbarrier::complete_tx::bytes [%0], [%1, {%3, %4}], [%2];"
                 :: "r"(dst), "l"(tm), "r"(bar), "r"(col), "r"(row) : "memory");
}
__device__ __forceinline__ void ldsm4(uint32_t (&r)[4], uint32_t addr) {
    asm volatile("ldmatrix.sync.aligned.m8n8.x4.shared.b16 {%0,%1,%2,%3}, [%4];"
                 : "=r"(r[0]), "=r"(r[1]), "=r"(r[2]), "=r"(r[3]) : "r"(addr));
}
__device__ __forceinline__ void ldsm4t(uint32_t (&r)[4], uint32_t addr) {
    asm volatile("ldmatrix.sync.aligned.m8n8.x4.trans.shared.b16 {%0,%1,%2,%3}, [%4];"
                 : "=r"(r[0]), "=r"(r[1]), "=r"(r[2]), "=r"(r[3]) : "r"(addr));
}
__device__ __forceinline__ void mma16816(float (&d)[4], uint32_t a0, uint32_t a1, uint32_t a2, uint32_t a3, uint32_t b0, uint32_t b1) {
    asm volatile("mma.sync.aligned.m16n8k16.row.col.f32.bf16.bf16.f32 {%0,%1,%2,%3}, {%4,%5,%6,%7}, {%8,%9}, {%0,%1,%2,%3};"
                 : "+f"(d[0]), "+f"(d[1]), "+f"(d[2]), "+f"(d[3]) : "r"(a0), "r"(a1), "r"(a2), "r"(a3), "r"(b0), "r"(b1));
}
__device__ __forceinline__ void sts2(uint32_t a, uint32_t x, uint32_t y) {
    asm volatile("st.shared.v2.b32 [%0], {%1,%2};" :: "r"(a), "r"(x), "r"(y) : "memory");
}
__device__ __forceinline__ void lds2(uint32_t& x, uint32_t& y, uint32_t a) {
    asm volatile("ld.shared.v2.b32 {%0,%1}, [%2];" : "=r"(x), "=r"(y) : "r"(a) : "memory");
}
__device__ __forceinline__ void sts4(uint32_t a, const float (&v)[4]) {
    asm volatile("st.shared.v4.f32 [%0], {%1,%2,%3,%4};" :: "r"(a), "f"(v[0]), "f"(v[1]), "f"(v[2]), "f"(v[3]) : "memory");
}
__device__ __forceinline__ void lds4(float (&v)[4], uint32_t a) {
    asm volatile("ld.shared.v4.f32 {%0,%1,%2,%3}, [%4];" : "=f"(v[0]), "=f"(v[1]), "=f"(v[2]), "=f"(v[3]) : "r"(a) : "memory");
}
__device__ __forceinline__ float ex2(float x) { float y; asm("ex2.approx.ftz.f32 %0, %1;" : "=f"(y) : "f"(x)); return y; }
__device__ __forceinline__ float rcp(float x) { float y; asm("rcp.approx.ftz.f32 %0, %1;" : "=f"(y) : "f"(x)); return y; }
__device__ __forceinline__ float expdiff(float a, float b) { return ex2((a - b) * kLog2e); }
__device__ __forceinline__ float sel(uint32_t c, float a, float b) {
    float r; asm("{\n.reg .pred p;\nsetp.ne.u32 p, %3, 0;\nselp.f32 %0, %1, %2, p;\n}" : "=f"(r) : "f"(a), "f"(b), "r"(c)); return r;
}
__device__ __forceinline__ uint32_t pack_bf16(float lo, float hi) {
    uint32_t r; asm("cvt.rn.bf16x2.f32 %0, %1, %2;" : "=r"(r) : "f"(hi), "f"(lo)); return r;
}
__device__ __forceinline__ float bf_lo(uint32_t v) { return __uint_as_float(v << 16); }
__device__ __forceinline__ float bf_hi(uint32_t v) { return __uint_as_float(v & 0xffff0000u); }
__device__ __forceinline__ float bf_round(float x) { return __bfloat162float(__float2bfloat16(x)); }
__device__ __forceinline__ uint32_t scale_scores(float a, float b) {
    const uint32_t r = pack_bf16(a, b);
    return pack_bf16(bf_lo(r) * kScale, bf_hi(r) * kScale);
}
__device__ __forceinline__ void st_bf16_if(__nv_bfloat16* p, float v, bool pred) {
    asm volatile("{\n.reg .pred p;\n.reg .b16 h;\nsetp.ne.u32 p, %2, 0;\ncvt.rn.bf16.f32 h, %1;\n@p st.global.b16 [%0], h;\n}"
                 :: "l"(p), "f"(v), "r"((uint32_t)pred) : "memory");
}
__device__ __forceinline__ void st_word(uint64_t* p, uint64_t v) {
    asm volatile("st.relaxed.gpu.global.b64 [%0], %1;" :: "l"(p), "l"(v) : "memory");
}
__device__ __forceinline__ void clear_word_if(uint64_t* p, bool pred) {
    asm volatile("{\n.reg .pred p;\nsetp.ne.u32 p, %1, 0;\n@p st.relaxed.gpu.global.b64 [%0], 0;\n}"
                 :: "l"(p), "r"((uint32_t)pred) : "memory");
}
__device__ __forceinline__ void ld_word_if(uint64_t& a, const uint64_t* p, bool pred) {
    asm volatile("{\n.reg .pred p;\nsetp.ne.u32 p, %2, 0;\n@p ld.relaxed.gpu.global.b64 %0, [%1];\n}"
                 : "+l"(a) : "l"(p), "r"((uint32_t)pred) : "memory");
}
__device__ __forceinline__ void ld_word2_if(uint64_t& a, uint64_t& b, const uint64_t* p, bool pred) {
    asm volatile("{\n.reg .pred p;\nsetp.ne.u32 p, %3, 0;\n@p ld.relaxed.gpu.global.v2.b64 {%0, %1}, [%2];\n}"
                 : "+l"(a), "+l"(b) : "l"(p), "r"((uint32_t)pred) : "memory");
}
__device__ __forceinline__ uint64_t make_word(uint32_t lo, uint32_t hi) {
    if (lo == 0u) lo = 0x80000000u;
    return ((uint64_t)hi << 32) | lo;
}
__device__ __forceinline__ uint64_t make_word(float lo, float hi) { return make_word(__float_as_uint(lo), __float_as_uint(hi)); }
__device__ __forceinline__ float word_lo(uint64_t w) { return __uint_as_float((uint32_t)w); }
__device__ __forceinline__ float word_hi(uint64_t w) { return __uint_as_float((uint32_t)(w >> 32)); }
__device__ __forceinline__ bool missing(uint64_t w) { return (uint32_t)w == 0u; }

struct Pace { int off, tau_q8, limit, tau_fb_q8; };

__global__ void __launch_bounds__(kThreads, 1)
tree_attn_decode_kernel(const __grid_constant__ CUtensorMap tmK, const __grid_constant__ CUtensorMap tmV,
                        const __grid_constant__ CUtensorMap tmStrip,
                        const __nv_bfloat16* __restrict__ q, const __nv_bfloat16* __restrict__ k_cache,
                        const __nv_bfloat16* __restrict__ k_tree, const __nv_bfloat16* __restrict__ v_tree,
                        const __nv_bfloat16* __restrict__ mask, __nv_bfloat16* __restrict__ out,
                        uint64_t* __restrict__ inboxes, Pace pace)
{
    const int row0 = blockIdx.x * kKeysPerCta;
    if (threadIdx.x == 0)
        asm volatile("cp.async.bulk.prefetch.L2.global [%0], %1;" :: "l"(k_cache + (size_t)row0 * kD), "n"(3 * kSlotBytes) : "memory");

    extern __shared__ uint8_t smem_raw[];
    const uint32_t sbase = (smem_u32(smem_raw) + 1023) & ~1023u;
    const uint32_t aux = sbase + kNS * kSlotBytes;
    const uint32_t full = aux + kOffBar, empty = full + kNS * 8;

    uint32_t t0 = 0;
    if (threadIdx.x == kNC) {
        t0 = timer_ns();
#pragma unroll
        for (int s = 0; s < kNS; s++) mbar_init(full + s * 8, 1);
        asm volatile("fence.mbarrier_init.release.cluster;" ::: "memory");
#pragma unroll
        for (int i = 0; i < 3; i++) {
            mbar_expect_tx(full + i * 8, kSlotBytes);
            tma_tile(sbase + i * kSlotBytes, &tmK, row0 + i * kTile, full + i * 8);
        }
#pragma unroll
        for (int s = 0; s < kNS; s++) mbar_init(empty + s * 8, kNW);
        sts2(aux + kOffPace, t0, 0u);
        sts2(aux + kOffPace + 8, (uint32_t)-kFar, 0u);
    }
    const int warp = threadIdx.x >> 5, lane = threadIdx.x & 31;
    const int pair = blockIdx.x >> 2, split = blockIdx.x & 3;

    if (warp == kNW) {
        __syncwarp();
        bar_arrive<1, kThreads>();
        if (lane == 0) {
#pragma unroll 1
            for (int i = 3; i < kNL; i++) {
                const int s = i % kNS;
                mbar_wait(empty + s * 8, ((i / kNS) & 1) ^ 1);
                if (i >= kFreeLoads) {
                    const int due = pace.off + (((i - kFreeLoads) * pace.tau_q8) >> 8);
                    const int ahead = ((i * pace.tau_fb_q8) >> 8) - pace.limit;
                    int phase, seen;
                    do {
                        asm volatile("ld.volatile.shared.v2.s32 {%0, %1}, [%2];" : "=r"(phase), "=r"(seen) : "r"(aux + kOffPace + 8) : "memory");
                    } while ((int)(timer_ns() - t0) < max(due, phase + ahead) && seen <= i - kMinInflight);
                }
                mbar_expect_tx(full + s * 8, kSlotBytes);
                if (i < kNL - kFin) {
                    const int j = i - kLead;
                    const bool is_k = i < kLead || (i < kNL - kLead && !(j & 1));
                    const int tile = i < kLead ? i : i >= kNL - kLead ? i - kNT : is_k ? kLead + (j >> 1) : (j >> 1);
                    tma_tile(sbase + s * kSlotBytes, is_k ? &tmK : &tmV, row0 + tile * kTile, full + s * 8);
                    if (i == kNL - 2 * kFin) asm volatile("prefetch.tensormap [%0];" :: "l"(&tmStrip) : "memory");
                } else {
                    tma_strip(sbase + s * kSlotBytes, &tmStrip, split * 32,
                              pair * kC + (i - (kNL - kFin) + 1) * kKeysPerCta - kFin * kTile, full + s * 8);
                }
            }
        }
        return;
    }

    const int tid = threadIdx.x;
    const int g = lane >> 2, t = lane & 3;

    uint32_t qa[8][2];
    {
        const uint32_t* qp = reinterpret_cast<const uint32_t*>(q + (size_t)(pair * 2 + (g & 1)) * kD);
#pragma unroll
        for (int j = 0; j < 8; j++) { qa[j][0] = __ldg(qp + j * 8 + t); qa[j][1] = __ldg(qp + j * 8 + 4 + t); }
    }
    uint64_t* boxes = inboxes + (size_t)pair * kSplit * kBoxWords;
    __nv_bfloat16* op = out + (size_t)(pair * 2 + (t & 1)) * kD + split * 32 + (warp & 1) * 16 + (t >> 1) * 8 + g;
    asm volatile("" : "+l"(boxes), "+l"(op));
    uint64_t* inbox = boxes + split * kBoxWords;
    auto outbox = [&](int r) { return boxes + r * kBoxWords + ((split - r - 1) & 3) * kSecWords; };

    float acc[8][4];
    float m = -INFINITY, l = 0.f;
#pragma unroll
    for (int j = 0; j < 8; j++) { acc[j][0] = acc[j][1] = acc[j][2] = acc[j][3] = 0.f; }
    if (split == kSplit - 1 && warp == 0) {
        const uint32_t* kp = reinterpret_cast<const uint32_t*>(k_tree + (size_t)pair * kD);
        const __nv_bfloat16* vp = v_tree + (size_t)pair * kD;
        float s4[4] = {0.f, 0.f, 0.f, 0.f};
#pragma unroll
        for (int j = 0; j < 8; j++) {
            mma16816(s4, qa[j][0], 0u, qa[j][1], 0u, __ldg(kp + j * 8 + t), __ldg(kp + j * 8 + 4 + t));
            acc[j][0] = acc[j][1] = __bfloat162float(vp[j * 16 + g]);
            acc[j][2] = acc[j][3] = __bfloat162float(vp[j * 16 + 8 + g]);
        }
        const float keep = __bfloat162float(mask[pair / kHkv]);
        m = bf_round(bf_lo(scale_scores(s4[0], s4[1])) + bf_round(bf_round(1.0f - keep) * -1000000000.0f));
        l = (t == 0) ? 1.f : 0.f;
    }

    const int r7 = lane & 7, mi = lane >> 3;
    const uint32_t ka0 = sbase + (uint32_t)(warp * 16 + r7) * 128 + ((mi ^ r7) << 4);
    const uint32_t ka1 = sbase + (uint32_t)(warp * 16 + r7) * 128 + (((4 + mi) ^ r7) << 4);
    uint32_t va[4];
#pragma unroll
    for (int jj = 0; jj < 4; jj++)
        va[jj] = sbase + (uint32_t)(warp * 16 + (mi >> 1) * 8 + r7) * 128 + (((jj * 2 + (mi & 1)) ^ r7) << 4);

    bar_sync<1, kThreads>();

    uint32_t tz, unused;
    lds2(tz, unused, aux + kOffPace);
    int seen = 0, ph_cur = kFar, ph_prev = -kFar;
    auto landed = [&]() {
        if (warp == 0) {
            ph_cur = min(ph_cur, (int)(timer_ns() - tz) - ((seen * pace.tau_q8) >> 8));
            if ((++seen & 3) == 0) { ph_prev = ph_cur; ph_cur = kFar; }
            if (lane == 0)
                asm volatile("st.volatile.shared.v2.s32 [%0], {%1, %2};" :: "r"(aux + kOffPace + 8), "r"(min(ph_cur, ph_prev)), "r"(seen) : "memory");
        }
    };
    auto release = [&](int s) {
        __syncwarp();
        if (lane == 0) mbar_arrive(empty + s * 8);
    };
    auto probs = [&](uint32_t& s01, uint32_t& s23) {
        const float p0 = expdiff(bf_lo(s01), m), p1 = expdiff(bf_hi(s01), m);
        const float p2 = expdiff(bf_lo(s23), m), p3 = expdiff(bf_hi(s23), m);
        l += (p0 + p1) + (p2 + p3);
        s01 = pack_bf16(p0, p1); s23 = pack_bf16(p2, p3);
    };
    auto pv = [&](int s, int parity, uint32_t b0, uint32_t b1) {
        uint32_t a[4];
#pragma unroll
        for (int jj = 0; jj < 4; jj++) a[jj] = va[jj] + s * kSlotBytes;
        asm volatile("" : "+r"(a[0]), "+r"(a[1]), "+r"(a[2]), "+r"(a[3]));
        mbar_wait(full + s * 8, parity);
        landed();
#pragma unroll
        for (int j = 0; j < 8; j++) {
            uint32_t r[4];
            ldsm4t(r, a[j & 3] + (j >> 2) * kHalf);
            mma16816(acc[j], r[0], r[1], r[2], r[3], b0, b1);
        }
    };

    uint32_t fifo[kLead + 1][2];
#pragma unroll
    for (int x = 0; x <= kLead; x++) fifo[x][0] = fifo[x][1] = 0u;
    int s = 0, ph = 0;
#pragma unroll 1
    for (int n = -kLead;; n++) {
#pragma unroll
        for (int x = 0; x < kLead; x++) { fifo[x][0] = fifo[x + 1][0]; fifo[x][1] = fifo[x + 1][1]; }
        {
            uint32_t a0 = ka0 + s * kSlotBytes, a1 = ka1 + s * kSlotBytes;
            asm volatile("" : "+r"(a0), "+r"(a1));
            mbar_wait(full + s * 8, ph);
            landed();
            float sc[2][2][4];
#pragma unroll
            for (int u = 0; u < 2; u++)
#pragma unroll
                for (int c = 0; c < 2; c++) sc[u][c][0] = sc[u][c][1] = sc[u][c][2] = sc[u][c][3] = 0.f;
#pragma unroll
            for (int qd = 0; qd < 4; qd++) {
#pragma unroll
                for (int u = 0; u < 2; u++) {
                    uint32_t r[4];
                    ldsm4(r, ((qd & 1) ? a1 : a0) + u * 1024 + (qd >> 1) * kHalf);
                    mma16816(sc[u][0], qa[2 * qd][0], 0u, qa[2 * qd][1], 0u, r[0], r[1]);
                    mma16816(sc[u][1], qa[2 * qd + 1][0], 0u, qa[2 * qd + 1][1], 0u, r[2], r[3]);
                }
            }
            release(s);
            if (++s == kNS) { s = 0; ph ^= 1; }
            const uint32_t s01 = scale_scores(sc[0][0][0] + sc[0][1][0], sc[0][0][1] + sc[0][1][1]);
            const uint32_t s23 = scale_scores(sc[1][0][0] + sc[1][1][0], sc[1][0][1] + sc[1][1][1]);
            fifo[kLead][0] = s01; fifo[kLead][1] = s23;
            float mx = fmaxf(fmaxf(bf_lo(s01), bf_hi(s01)), fmaxf(bf_lo(s23), bf_hi(s23)));
            mx = fmaxf(mx, __shfl_xor_sync(0xffffffffu, mx, 1));
            mx = fmaxf(mx, __shfl_xor_sync(0xffffffffu, mx, 2));
            if (__any_sync(0xffffffffu, mx > m)) {
                const float mn = fmaxf(m, mx);
                const float f = expdiff(m, mn), fo = __shfl_xor_sync(0xffffffffu, f, 4);
                const float f0 = (g & 1) ? fo : f, f1 = (g & 1) ? f : fo;
                m = mn; l *= f;
#pragma unroll
                for (int j = 0; j < 8; j++) { acc[j][0] *= f0; acc[j][1] *= f1; acc[j][2] *= f0; acc[j][3] *= f1; }
            }
        }
        if (n == kNT - kLead - 1) break;
        if (n >= 0) {
            probs(fifo[0][0], fifo[0][1]);
            pv(s, ph, fifo[0][0], fifo[0][1]);
            release(s);
            if (++s == kNS) { s = 0; ph ^= 1; }
        }
    }

    float f0[kNW], f1[kNW], sM0 = -INFINITY, sM1 = -INFINITY, sL0 = 0.f, sL1 = 0.f;
    {
        uint64_t* ob = outbox((split + 1 + (g >> 1)) & 3);
#pragma unroll
        for (int u = 0; u < kFin; u++) {
            const int wd = (u * kNW + warp) * 8 + (g & 1) * 4 + t;
            if ((g >> 1) < 3) st_word(ob + kSecScore + wd, make_word(fifo[kEarly + u][0], fifo[kEarly + u][1]));
            else sts2(aux + kOffP + split * 1024 + wd * 8, fifo[kEarly + u][0], fifo[kEarly + u][1]);
        }
#pragma unroll
        for (int x = 0; x <= kLead; x++) probs(fifo[x][0], fifo[x][1]);
        float lr = l + __shfl_xor_sync(0xffffffffu, l, 1);
        lr += __shfl_xor_sync(0xffffffffu, lr, 2);
        if (t == 0 && g < 2) sts2(aux + kOffMl + warp * 16 + g * 8, __float_as_uint(m), __float_as_uint(lr));
        bar_sync<2, kNC>();
        float mm[kNW][4];
#pragma unroll
        for (int w = 0; w < kNW; w++) {
            lds4(mm[w], aux + kOffMl + w * 16);
            sM0 = fmaxf(sM0, mm[w][0]); sM1 = fmaxf(sM1, mm[w][2]);
        }
#pragma unroll
        for (int w = 0; w < kNW; w++) {
            f0[w] = expdiff(mm[w][0], sM0); f1[w] = expdiff(mm[w][2], sM1);
            sL0 = fmaf(f0[w], mm[w][1], sL0); sL1 = fmaf(f1[w], mm[w][3], sL1);
        }
        if (warp == 0 && (g >> 1) < 3 && !(g & 1))
            st_word(ob + kSecStat + t, (t & 1) ? make_word(sL0, sL1) : make_word(sM0, sM1));
    }

    uint64_t sw[3] = {0ull, 0ull, 0ull}, wm[3] = {0ull, 0ull, 0ull}, wl[3] = {0ull, 0ull, 0ull};
#pragma unroll
    for (int x = 0; x < kEarly; x++) {
        const int i = kNL - 1 - kLead + x;
        if (x == kEarly - 3) {
#pragma unroll
            for (int y = 0; y < 3; y++) {
                ld_word_if(sw[y], inbox + y * kSecWords + kSecScore + tid, true);
                ld_word2_if(wm[y], wl[y], inbox + y * kSecWords + kSecStat, true);
            }
        }
        pv(i % kNS, (i / kNS) & 1, fifo[x][0], fifo[x][1]);
        if (i + kNS < kNL) release(i % kNS);
    }

    if (t == 0) {
#pragma unroll
        for (int j = 0; j < 8; j++) sts4(aux + kOffAcc + warp * 1024 + j * 128 + g * 16, acc[j]);
    }
    bar_sync<2, kNC>();
    if (warp != split) {
        float o0 = 0.f, o1 = 0.f;
#pragma unroll
        for (int w = 0; w < kNW; w++) {
            uint32_t a0, a1;
            lds2(a0, a1, aux + kOffAcc + w * 1024 + (tid >> 4) * 128 + (tid & 7) * 16 + ((tid >> 3) & 1) * 8);
            o0 = fmaf(f0[w], __uint_as_float(a0), o0); o1 = fmaf(f1[w], __uint_as_float(a1), o1);
        }
        st_word(outbox(warp) + kSecOut + lane, make_word(o0 * rcp(sL0), o1 * rcp(sL1)));
    }

#pragma unroll 1
    for (int it = 0;; it++) {
        bool ms[3], mt[3];
#pragma unroll
        for (int y = 0; y < 3; y++) { ms[y] = missing(sw[y]); mt[y] = missing(wm[y]) || missing(wl[y]); }
        if (!(ms[0] || ms[1] || ms[2] || mt[0] || mt[1] || mt[2])) break;
        if (it > (1 << 22)) __trap();
#pragma unroll
        for (int y = 0; y < 3; y++) {
            ld_word_if(sw[y], inbox + y * kSecWords + kSecScore + tid, ms[y]);
            ld_word2_if(wm[y], wl[y], inbox + y * kSecWords + kSecStat, mt[y]);
        }
    }
    __syncwarp();
    float wy[3];
    {
        const float M0 = fmaxf(fmaxf(sM0, word_lo(wm[0])), fmaxf(word_lo(wm[1]), word_lo(wm[2])));
        const float M1 = fmaxf(fmaxf(sM1, word_hi(wm[0])), fmaxf(word_hi(wm[1]), word_hi(wm[2])));
        float c0[3], c1[3];
#pragma unroll
        for (int y = 0; y < 3; y++) {
            c0[y] = expdiff(word_lo(wm[y]), M0) * word_lo(wl[y]);
            c1[y] = expdiff(word_hi(wm[y]), M1) * word_hi(wl[y]);
        }
        const float e0 = expdiff(sM0, M0), e1 = expdiff(sM1, M1);
        const float r0 = rcp((c0[0] + c0[2]) + (c0[1] + e0 * sL0)), r1 = rcp((c1[0] + c1[2]) + (c1[1] + e1 * sL1));
#pragma unroll
        for (int y = 0; y < 3; y++) wy[y] = (t & 1) ? c1[y] * r1 : c0[y] * r0;
#pragma unroll
        for (int w = 0; w < kNW; w++) { f0[w] *= e0 * r0; f1[w] *= e1 * r1; }
        const float Mh = (tid & 4) ? M1 : M0, rh = (tid & 4) ? r1 : r0;
#pragma unroll
        for (int y = 0; y < kSplit; y++) {
            const uint32_t pa = aux + kOffP + ((split + 1 + y) & 3) * 1024 + tid * 8;
            uint32_t s01, s23;
            if (y < 3) {
                s01 = (uint32_t)sw[y]; s23 = (uint32_t)(sw[y] >> 32);
                st_word(inbox + y * kSecWords + kSecScore + tid, 0ull);
            } else {
                lds2(s01, s23, pa);
            }
            sts2(pa, pack_bf16(expdiff(bf_lo(s01), Mh) * rh, expdiff(bf_hi(s01), Mh) * rh),
                     pack_bf16(expdiff(bf_lo(s23), Mh) * rh, expdiff(bf_hi(s23), Mh) * rh));
        }
    }
    bar_sync<2, kNC>();
    if (warp == 3 && lane < 12) st_word(inbox + (lane >> 2) * kSecWords + kSecStat + (lane & 3), 0ull);
    if (warp >= 2) return;

    float c[4][4];
#pragma unroll
    for (int k = 0; k < 4; k++) c[k][0] = c[k][1] = c[k][2] = c[k][3] = 0.f;
#pragma unroll
    for (int w = 0; w < kNW; w++) {
        float v[4];
        lds4(v, aux + kOffAcc + w * 1024 + (split * 2 + warp) * 128 + g * 16);
        c[0][0] = fmaf(f0[w], v[0], c[0][0]); c[0][1] = fmaf(f1[w], v[1], c[0][1]);
        c[0][2] = fmaf(f0[w], v[2], c[0][2]); c[0][3] = fmaf(f1[w], v[3], c[0][3]);
    }
    uint32_t la = sbase + (uint32_t)((mi >> 1) * 8 + r7) * 64 + (((warp * 2 + (mi & 1)) ^ (r7 >> 1)) << 4);
    uint64_t* oin = inbox + kSecOut + warp * 16 + (t >> 1) * 8 + g;
    uint64_t ow[3] = {0ull, 0ull, 0ull};
    bool late = false;
    asm volatile("" : "+r"(la), "+l"(oin), "+l"(ow[0]), "+l"(ow[1]), "+l"(ow[2]));
#pragma unroll
    for (int x = 0; x < kSplit; x++) {
        const int i = kNL - kFin + x;
        uint32_t pb[16][2];
#pragma unroll
        for (int k = 0; k < 16; k++) lds2(pb[k][0], pb[k][1], aux + kOffP + x * 1024 + k * 64 + (g & 1) * 32 + t * 8);
        if (x == kSplit - 1) {
#pragma unroll
            for (int y = 0; y < 3; y++) ld_word_if(ow[y], oin + y * kSecWords, true);
        }
        mbar_wait(full + (i % kNS) * 8, (i / kNS) & 1);
#pragma unroll
        for (int k = 0; k < 16; k++) {
            uint32_t r[4];
            ldsm4t(r, la + (i % kNS) * kSlotBytes + k * 1024);
            mma16816(c[k & 3], r[0], r[1], r[2], r[3], pb[k][0], pb[k][1]);
            if (x == kSplit - 1 && k == 4) {
                late = __any_sync(0xffffffffu, missing(ow[0]) || missing(ow[1]) || missing(ow[2]));
#pragma unroll
                for (int y = 0; y < 3; y++) clear_word_if(oin + y * kSecWords, !late && !(t & 1));
            }
        }
    }
    const uint32_t t1 = t & 1, t2 = t & 2;
    const float o = (sel(t2, sel(t1, c[0][3], c[0][2]), sel(t1, c[0][1], c[0][0])) + sel(t2, sel(t1, c[1][3], c[1][2]), sel(t1, c[1][1], c[1][0])))
                  + (sel(t2, sel(t1, c[2][3], c[2][2]), sel(t1, c[2][1], c[2][0])) + sel(t2, sel(t1, c[3][3], c[3][2]), sel(t1, c[3][1], c[3][0])));
    auto remote = [&]() {
        return fmaf(wy[0], sel(t1, word_hi(ow[0]), word_lo(ow[0])),
               fmaf(wy[1], sel(t1, word_hi(ow[1]), word_lo(ow[1])), wy[2] * sel(t1, word_hi(ow[2]), word_lo(ow[2]))));
    };
    st_bf16_if(op, o + remote(), !late);
    if (late) {
#pragma unroll 1
        for (int it = 0; missing(ow[0]) || missing(ow[1]) || missing(ow[2]); it++) {
            if (it > (1 << 22)) __trap();
#pragma unroll
            for (int y = 0; y < 3; y++) ld_word_if(ow[y], oin + y * kSecWords, missing(ow[y]));
        }
        st_bf16_if(op, o + remote(), true);
        __syncwarp();
#pragma unroll
        for (int y = 0; y < 3; y++) clear_word_if(oin + y * kSecWords, !t1);
    }
}

typedef CUresult (*EncodeTiledFn)(CUtensorMap*, CUtensorMapDataType, cuuint32_t, void*, const cuuint64_t*, const cuuint64_t*,
                                  const cuuint32_t*, const cuuint32_t*, CUtensorMapInterleave, CUtensorMapSwizzle,
                                  CUtensorMapL2promotion, CUtensorMapFloatOOBfill);

CUtensorMap make_tile_map(EncodeTiledFn encode, void* base) {
    CUtensorMap m;
    const cuuint64_t dims[3] = {64, (cuuint64_t)kPairs * kC, 2};
    const cuuint64_t strides[2] = {256, 128};
    const cuuint32_t box[3] = {64, (cuuint32_t)kTile, 2};
    const cuuint32_t elem[3] = {1, 1, 1};
    encode(&m, CU_TENSOR_MAP_DATA_TYPE_BFLOAT16, 3, base, dims, strides, box, elem, CU_TENSOR_MAP_INTERLEAVE_NONE,
           CU_TENSOR_MAP_SWIZZLE_128B, CU_TENSOR_MAP_L2_PROMOTION_L2_256B, CU_TENSOR_MAP_FLOAT_OOB_FILL_NONE);
    return m;
}

CUtensorMap make_strip_map(EncodeTiledFn encode, void* base) {
    CUtensorMap m;
    const cuuint64_t dims[2] = {(cuuint64_t)kD, (cuuint64_t)kPairs * kC};
    const cuuint64_t strides[1] = {256};
    const cuuint32_t box[2] = {32, (cuuint32_t)(kFin * kTile)};
    const cuuint32_t elem[2] = {1, 1};
    encode(&m, CU_TENSOR_MAP_DATA_TYPE_BFLOAT16, 2, base, dims, strides, box, elem, CU_TENSOR_MAP_INTERLEAVE_NONE,
           CU_TENSOR_MAP_SWIZZLE_64B, CU_TENSOR_MAP_L2_PROMOTION_L2_256B, CU_TENSOR_MAP_FLOAT_OOB_FILL_NONE);
    return m;
}

}

extern "C" void kernel_launch(void* const* d_in, const int* in_sizes, int n_in, void* d_out, int out_size) {
    (void)in_sizes; (void)n_in; (void)out_size;
    static EncodeTiledFn encode = nullptr;
    static void* inboxes = nullptr;
    static Pace pace = {0, 0, 0, 0};
    if (!encode) {
        cudaDriverEntryPointQueryResult qr;
        cudaGetDriverEntryPoint("cuTensorMapEncodeTiled", (void**)&encode, cudaEnableDefault, &qr);
        cudaFuncSetAttribute(tree_attn_decode_kernel, cudaFuncAttributeMaxDynamicSharedMemorySize, kSmemBytes);
        cudaGetSymbolAddress(&inboxes, g_inbox);
        int dev = 0, mem_khz = 0, bus_bits = 0;
        cudaGetDevice(&dev);
        cudaDeviceGetAttribute(&mem_khz, cudaDevAttrMemoryClockRate, dev);
        cudaDeviceGetAttribute(&bus_bits, cudaDevAttrGlobalMemoryBusWidth, dev);
        const double bytes_per_ns = 2.0 * mem_khz * 1e-6 * bus_bits / 8.0;
        if (bytes_per_ns > 0.0) {
            const double tau = (double)kPairs * kSplit * kSlotBytes / (0.9595 * bytes_per_ns);
            pace = {(int)(2.0 * tau), (int)(tau * 256.0), (int)(4.14 * tau), (int)(1.02 * tau * 256.0)};
        }
    }
    const CUtensorMap tmK = make_tile_map(encode, d_in[1]);
    const CUtensorMap tmV = make_tile_map(encode, d_in[2]);
    const CUtensorMap tmStrip = make_strip_map(encode, d_in[2]);
    tree_attn_decode_kernel<<<kPairs * kSplit, kThreads, kSmemBytes>>>(
        tmK, tmV, tmStrip, (const __nv_bfloat16*)d_in[0], (const __nv_bfloat16*)d_in[1], (const __nv_bfloat16*)d_in[3],
        (const __nv_bfloat16*)d_in[4], (const __nv_bfloat16*)d_in[5], (__nv_bfloat16*)d_out, (uint64_t*)inboxes, pace);
}
```

```cpp
#include <cuda_runtime.h>
#include <cuda_bf16.h>
#include <cuda.h>
#include <stdint.h>

namespace {

constexpr int kB = 2, kHkv = 16, kC = 8192, kD = 128;
constexpr int kPairs = kB * kHkv;
constexpr int kSplit = 4;
constexpr int kKeysPerCta = kC / kSplit;
constexpr int kTile = 64;
constexpr int kNW = kTile / 16;
constexpr int kNC = kNW * 32;
constexpr int kThreads = kNC + 32;
constexpr int kNS = 8;
constexpr int kNT = kKeysPerCta / kTile;
constexpr int kNL = 2 * kNT;
constexpr int kLead = 10;
constexpr int kFin = 4;
constexpr int kEarly = kLead + 1 - kFin;
constexpr int kSlotBytes = kTile * kD * 2;
constexpr uint32_t kHalf = kTile * 128;
constexpr int kFreeLoads = 4;
constexpr int kMinInflight = 2;
constexpr int kFar = 1 << 29;
constexpr float kScale = 0.08838834764831845f;
constexpr float kLog2e = 1.4426950408889634f;
constexpr uint32_t kOffAcc = 0;
constexpr uint32_t kOffMl = kOffAcc + kNW * 1024;
constexpr uint32_t kOffP = kOffMl + kNW * 16;
constexpr uint32_t kOffPace = kOffP + kSplit * 1024;
constexpr uint32_t kOffBar = kOffPace + 16;
constexpr int kSmemBytes = 1024   + kNS * kSlotBytes + kOffBar + 2 * kNS * 8;
static_assert(kNC == kD && kSplit == 4 && kNW == 4 && kFin == 4, "layout assumptions");
static_assert(kLead >= 3 && kEarly >= 3 && kFin <= kNS, "load order assumptions");

constexpr int kSecScore = 0;
constexpr int kSecStat = 128;
constexpr int kSecOut = 144;
constexpr int kSecWords = 176;
constexpr int kBoxWords = 3 * kSecWords;
__device__ __align__(128) uint64_t g_inbox[kPairs * kSplit * kBoxWords];

__device__ __forceinline__ uint32_t smem_u32(const void* p) { return (uint32_t)__cvta_generic_to_shared(p); }
__device__ __forceinline__ uint32_t timer_ns() { uint32_t t; asm volatile("mov.u32 %0, %globaltimer_lo;" : "=r"(t)); return t; }
__device__ __forceinline__ void mbar_init(uint32_t bar, uint32_t cnt) {
    asm volatile("mbarrier.init.shared::cta.b64 [%0], %1;" :: "r"(bar), "r"(cnt) : "memory");
}
__device__ __forceinline__ void mbar_expect_tx(uint32_t bar, uint32_t bytes) {
    asm volatile("mbarrier.arrive.expect_tx.shared::cta.b64 _, [%0], %1;" :: "r"(bar), "r"(bytes) : "memory");
}
__device__ __forceinline__ void mbar_arrive(uint32_t bar) {
    asm volatile("mbarrier.arrive.shared::cta.b64 _, [%0];" :: "r"(bar) : "memory");
}
__device__ __forceinline__ void mbar_wait(uint32_t bar, uint32_t parity) {
    asm volatile(
        "{\n"
        ".reg .pred p, q;\n"
        ".reg .u32 c;\n"
        "mov.u32 c, 0;\n"
        "LAB_WAIT:\n"
        "mbarrier.try_wait.parity.shared::cta.b64 p, [%0], %1;\n"
        "@p bra LAB_DONE;\n"
        "add.u32 c, c, 1;\n"
        "setp.lt.u32 q, c, 0x1000000;\n"
        "@q bra LAB_WAIT;\n"
        "trap;\n"
        "LAB_DONE:\n"
        "}\n" :: "r"(bar), "r"(parity) : "memory");
}
template <int ID, int N> __device__ __forceinline__ void bar_sync() { asm volatile("bar.sync %0, %1;" :: "n"(ID), "n"(N) : "memory"); }
template <int ID, int N> __device__ __forceinline__ void bar_arrive() { asm volatile("bar.arrive %0, %1;" :: "n"(ID), "n"(N) : "memory"); }
__device__ __forceinline__ void tma_tile(uint32_t dst, const CUtensorMap* tm, int array, int row, uint32_t bar) {
    asm volatile("cp.async.bulk.tensor.4d.shared::cluster.global.mbarrier::complete_tx::bytes [%0], [%1, {%3, %4, %3, %5}], [%2];"
                 :: "r"(dst), "l"(tm), "r"(bar), "r"(0), "r"(row), "r"(array) : "memory");
}
__device__ __forceinline__ void tma_strip(uint32_t dst, const CUtensorMap* tm, int col, int row, uint32_t bar) {
    asm volatile("cp.async.bulk.tensor.2d.shared::cluster.global.mbarrier::complete_tx::bytes [%0], [%1, {%3, %4}], [%2];"
                 :: "r"(dst), "l"(tm), "r"(bar), "r"(col), "r"(row) : "memory");
}
__device__ __forceinline__ void ldsm4(uint32_t (&r)[4], uint32_t addr) {
    asm volatile("ldmatrix.sync.aligned.m8n8.x4.shared.b16 {%0,%1,%2,%3}, [%4];"
                 : "=r"(r[0]), "=r"(r[1]), "=r"(r[2]), "=r"(r[3]) : "r"(addr));
}
__device__ __forceinline__ void ldsm4t(uint32_t (&r)[4], uint32_t addr) {
    asm volatile("ldmatrix.sync.aligned.m8n8.x4.trans.shared.b16 {%0,%1,%2,%3}, [%4];"
                 : "=r"(r[0]), "=r"(r[1]), "=r"(r[2]), "=r"(r[3]) : "r"(addr));
}
__device__ __forceinline__ void mma16816(float (&d)[4], uint32_t a0, uint32_t a1, uint32_t a2, uint32_t a3, uint32_t b0, uint32_t b1) {
    asm volatile("mma.sync.aligned.m16n8k16.row.col.f32.bf16.bf16.f32 {%0,%1,%2,%3}, {%4,%5,%6,%7}, {%8,%9}, {%0,%1,%2,%3};"
                 : "+f"(d[0]), "+f"(d[1]), "+f"(d[2]), "+f"(d[3]) : "r"(a0), "r"(a1), "r"(a2), "r"(a3), "r"(b0), "r"(b1));
}
__device__ __forceinline__ void sts2(uint32_t a, uint32_t x, uint32_t y) {
    asm volatile("st.shared.v2.b32 [%0], {%1,%2};" :: "r"(a), "r"(x), "r"(y) : "memory");
}
__device__ __forceinline__ void lds2(uint32_t& x, uint32_t& y, uint32_t a) {
    asm volatile("ld.shared.v2.b32 {%0,%1}, [%2];" : "=r"(x), "=r"(y) : "r"(a) : "memory");
}
__device__ __forceinline__ void sts4(uint32_t a, const float (&v)[4]) {
    asm volatile("st.shared.v4.f32 [%0], {%1,%2,%3,%4};" :: "r"(a), "f"(v[0]), "f"(v[1]), "f"(v[2]), "f"(v[3]) : "memory");
}
__device__ __forceinline__ void lds4(float (&v)[4], uint32_t a) {
    asm volatile("ld.shared.v4.f32 {%0,%1,%2,%3}, [%4];" : "=f"(v[0]), "=f"(v[1]), "=f"(v[2]), "=f"(v[3]) : "r"(a) : "memory");
}
__device__ __forceinline__ float ex2(float x) { float y; asm("ex2.approx.ftz.f32 %0, %1;" : "=f"(y) : "f"(x)); return y; }
__device__ __forceinline__ float rcp(float x) { float y; asm("rcp.approx.ftz.f32 %0, %1;" : "=f"(y) : "f"(x)); return y; }
__device__ __forceinline__ float expdiff(float a, float b) { return ex2((a - b) * kLog2e); }
__device__ __forceinline__ float sel(uint32_t c, float a, float b) {
    float r; asm("{\n.reg .pred p;\nsetp.ne.u32 p, %3, 0;\nselp.f32 %0, %1, %2, p;\n}" : "=f"(r) : "f"(a), "f"(b), "r"(c)); return r;
}
__device__ __forceinline__ uint32_t pack_bf16(float lo, float hi) {
    uint32_t r; asm("cvt.rn.bf16x2.f32 %0, %1, %2;" : "=r"(r) : "f"(hi), "f"(lo)); return r;
}
__device__ __forceinline__ float bf_lo(uint32_t v) { return __uint_as_float(v << 16); }
__device__ __forceinline__ float bf_hi(uint32_t v) { return __uint_as_float(v & 0xffff0000u); }
__device__ __forceinline__ float bf_round(float x) { return __bfloat162float(__float2bfloat16(x)); }
__device__ __forceinline__ uint32_t scale_scores(float a, float b) {
    const uint32_t r = pack_bf16(a, b);
    return pack_bf16(bf_lo(r) * kScale, bf_hi(r) * kScale);
}
__device__ __forceinline__ void st_bf16_if(__nv_bfloat16* p, float v, bool pred) {
    asm volatile("{\n.reg .pred p;\n.reg .b16 h;\nsetp.ne.u32 p, %2, 0;\ncvt.rn.bf16.f32 h, %1;\n@p st.global.b16 [%0], h;\n}"
                 :: "l"(p), "f"(v), "r"((uint32_t)pred) : "memory");
}
__device__ __forceinline__ void st_word(uint64_t* p, uint64_t v) {
    asm volatile("st.relaxed.gpu.global.b64 [%0], %1;" :: "l"(p), "l"(v) : "memory");
}
__device__ __forceinline__ void clear_word_if(uint64_t* p, bool pred) {
    asm volatile("{\n.reg .pred p;\nsetp.ne.u32 p, %1, 0;\n@p st.relaxed.gpu.global.b64 [%0], 0;\n}"
                 :: "l"(p), "r"((uint32_t)pred) : "memory");
}
__device__ __forceinline__ void ld_word_if(uint64_t& a, const uint64_t* p, bool pred) {
    asm volatile("{\n.reg .pred p;\nsetp.ne.u32 p, %2, 0;\n@p ld.relaxed.gpu.global.b64 %0, [%1];\n}"
                 : "+l"(a) : "l"(p), "r"((uint32_t)pred) : "memory");
}
__device__ __forceinline__ void ld_word2_if(uint64_t& a, uint64_t& b, const uint64_t* p, bool pred) {
    asm volatile("{\n.reg .pred p;\nsetp.ne.u32 p, %3, 0;\n@p ld.relaxed.gpu.global.v2.b64 {%0, %1}, [%2];\n}"
                 : "+l"(a), "+l"(b) : "l"(p), "r"((uint32_t)pred) : "memory");
}
__device__ __forceinline__ uint64_t make_word(uint32_t lo, uint32_t hi) {
    if (lo == 0u) lo = 0x80000000u;
    return ((uint64_t)hi << 32) | lo;
}
__device__ __forceinline__ uint64_t make_word(float lo, float hi) { return make_word(__float_as_uint(lo), __float_as_uint(hi)); }
__device__ __forceinline__ float word_lo(uint64_t w) { return __uint_as_float((uint32_t)w); }
__device__ __forceinline__ float word_hi(uint64_t w) { return __uint_as_float((uint32_t)(w >> 32)); }
__device__ __forceinline__ bool missing(uint64_t w) { return (uint32_t)w == 0u; }

struct Pace { int off, tau_q8, limit, tau_fb_q8; };

struct OneMap {
    CUtensorMap kv, strip;
    __device__ void load(uint32_t dst, bool is_k, int k_index, int row, uint32_t bar) const {
        tma_tile(dst, &kv, is_k ? k_index : 1 - k_index, row, bar);
    }
};
struct TwoMaps {
    CUtensorMap k, v, strip;
    __device__ void load(uint32_t dst, bool is_k, int, int row, uint32_t bar) const { tma_tile(dst, is_k ? &k : &v, 0, row, bar); }
};

template <class Maps>
__global__ void __launch_bounds__(kThreads, 1)
tree_attn_decode_kernel(const __nv_bfloat16* __restrict__ k_cache, const __nv_bfloat16* __restrict__ q,
                        const __nv_bfloat16* __restrict__ k_tree, const __nv_bfloat16* __restrict__ v_tree,
                        const __nv_bfloat16* __restrict__ mask, __nv_bfloat16* __restrict__ out,
                        const __grid_constant__ Maps maps, uint64_t* __restrict__ inboxes, Pace pace, int k_index)
{
    const int row0 = blockIdx.x * kKeysPerCta;
    if (threadIdx.x == 0)
        asm volatile("cp.async.bulk.prefetch.L2.global [%0], %1;" :: "l"(k_cache + (size_t)row0 * kD), "n"(3 * kSlotBytes) : "memory");

    extern __shared__ uint8_t smem_raw[];
    const uint32_t sbase = (smem_u32(smem_raw) + 1023) & ~1023u;
    const uint32_t aux = sbase + kNS * kSlotBytes;
    const uint32_t full = aux + kOffBar, empty = full + kNS * 8;

    uint32_t t0 = 0;
    if (threadIdx.x == kNC) {
        t0 = timer_ns();
#pragma unroll
        for (int s = 0; s < kNS; s++) mbar_init(full + s * 8, 1);
        asm volatile("fence.mbarrier_init.release.cluster;" ::: "memory");
#pragma unroll
        for (int i = 0; i < 3; i++) {
            mbar_expect_tx(full + i * 8, kSlotBytes);
            maps.load(sbase + i * kSlotBytes, true, k_index, row0 + i * kTile, full + i * 8);
        }
#pragma unroll
        for (int s = 0; s < kNS; s++) mbar_init(empty + s * 8, kNW);
        sts2(aux + kOffPace, t0, 0u);
        sts2(aux + kOffPace + 8, (uint32_t)-kFar, 0u);
    }
    const int warp = threadIdx.x >> 5, lane = threadIdx.x & 31;
    const int pair = blockIdx.x >> 2, split = blockIdx.x & 3;

    if (warp == kNW) {
        __syncwarp();
        bar_arrive<1, kThreads>();
        if (lane == 0) {
#pragma unroll 1
            for (int i = 3; i < kNL; i++) {
                const int s = i % kNS;
                mbar_wait(empty + s * 8, ((i / kNS) & 1) ^ 1);
                if (i >= kFreeLoads) {
                    const int due = pace.off + (((i - kFreeLoads) * pace.tau_q8) >> 8);
                    const int ahead = ((i * pace.tau_fb_q8) >> 8) - pace.limit;
                    int phase, seen, spins = 0;
                    do {
                        asm volatile("ld.volatile.shared.v2.s32 {%0, %1}, [%2];" : "=r"(phase), "=r"(seen) : "r"(aux + kOffPace + 8) : "memory");
                    } while ((int)(timer_ns() - t0) < max(due, phase + ahead) && seen <= i - kMinInflight && ++spins < (1 << 16));
                }
                mbar_expect_tx(full + s * 8, kSlotBytes);
                if (i < kNL - kFin) {
                    const int j = i - kLead;
                    const bool is_k = i < kLead || (i < kNL - kLead && !(j & 1));
                    const int tile = i < kLead ? i : i >= kNL - kLead ? i - kNT : is_k ? kLead + (j >> 1) : (j >> 1);
                    maps.load(sbase + s * kSlotBytes, is_k, k_index, row0 + tile * kTile, full + s * 8);
                    if (i == kNL - 2 * kFin) asm volatile("prefetch.tensormap [%0];" :: "l"(&maps.strip) : "memory");
                } else {
                    tma_strip(sbase + s * kSlotBytes, &maps.strip, split * 32,
                              pair * kC + (i - (kNL - kFin) + 1) * kKeysPerCta - kFin * kTile, full + s * 8);
                }
            }
        }
        return;
    }

    const int tid = threadIdx.x;
    const int g = lane >> 2, t = lane & 3;

    uint32_t qa[8][2];
    {
        const uint32_t* qp = reinterpret_cast<const uint32_t*>(q + (size_t)(pair * 2 + (g & 1)) * kD);
#pragma unroll
        for (int j = 0; j < 8; j++) { qa[j][0] = __ldg(qp + j * 8 + t); qa[j][1] = __ldg(qp + j * 8 + 4 + t); }
    }
    uint64_t* boxes = inboxes + (size_t)pair * kSplit * kBoxWords;
    __nv_bfloat16* op = out + (size_t)(pair * 2 + (t & 1)) * kD + split * 32 + (warp & 1) * 16 + (t >> 1) * 8 + g;
    asm volatile("" : "+l"(boxes), "+l"(op));
    uint64_t* inbox = boxes + split * kBoxWords;
    auto outbox = [&](int r) { return boxes + r * kBoxWords + ((split - r - 1) & 3) * kSecWords; };

    float acc[8][4];
    float m = -INFINITY, l = 0.f;
#pragma unroll
    for (int j = 0; j < 8; j++) { acc[j][0] = acc[j][1] = acc[j][2] = acc[j][3] = 0.f; }
    if (split == kSplit - 1 && warp == 0) {
        const uint32_t* kp = reinterpret_cast<const uint32_t*>(k_tree + (size_t)pair * kD);
        const __nv_bfloat16* vp = v_tree + (size_t)pair * kD;
        float s4[4] = {0.f, 0.f, 0.f, 0.f};
#pragma unroll
        for (int j = 0; j < 8; j++) {
            mma16816(s4, qa[j][0], 0u, qa[j][1], 0u, __ldg(kp + j * 8 + t), __ldg(kp + j * 8 + 4 + t));
            acc[j][0] = acc[j][1] = __bfloat162float(vp[j * 16 + g]);
            acc[j][2] = acc[j][3] = __bfloat162float(vp[j * 16 + 8 + g]);
        }
        const float keep = __bfloat162float(mask[pair / kHkv]);
        m = bf_round(bf_lo(scale_scores(s4[0], s4[1])) + bf_round(bf_round(1.0f - keep) * -1000000000.0f));
        l = (t == 0) ? 1.f : 0.f;
    }

    const int r7 = lane & 7, mi = lane >> 3;
    const uint32_t ka0 = sbase + (uint32_t)(warp * 16 + r7) * 128 + ((mi ^ r7) << 4);
    const uint32_t ka1 = sbase + (uint32_t)(warp * 16 + r7) * 128 + (((4 + mi) ^ r7) << 4);
    uint32_t va[4];
#pragma unroll
    for (int jj = 0; jj < 4; jj++)
        va[jj] = sbase + (uint32_t)(warp * 16 + (mi >> 1) * 8 + r7) * 128 + (((jj * 2 + (mi & 1)) ^ r7) << 4);

    bar_sync<1, kThreads>();

    uint32_t tz, unused;
    lds2(tz, unused, aux + kOffPace);
    int seen = 0, ph_cur = kFar, ph_prev = -kFar;
    auto landed = [&]() {
        if (warp == 0) {
            ph_cur = min(ph_cur, (int)(timer_ns() - tz) - ((seen * pace.tau_q8) >> 8));
            if ((++seen & 3) == 0) { ph_prev = ph_cur; ph_cur = kFar; }
            if (lane == 0)
                asm volatile("st.volatile.shared.v2.s32 [%0], {%1, %2};" :: "r"(aux + kOffPace + 8), "r"(min(ph_cur, ph_prev)), "r"(seen) : "memory");
        }
    };
    auto release = [&](int s) {
        __syncwarp();
        if (lane == 0) mbar_arrive(empty + s * 8);
    };
    auto probs = [&](uint32_t& s01, uint32_t& s23) {
        const float p0 = expdiff(bf_lo(s01), m), p1 = expdiff(bf_hi(s01), m);
        const float p2 = expdiff(bf_lo(s23), m), p3 = expdiff(bf_hi(s23), m);
        l += (p0 + p1) + (p2 + p3);
        s01 = pack_bf16(p0, p1); s23 = pack_bf16(p2, p3);
    };
    auto pv = [&](int s, int parity, uint32_t b0, uint32_t b1) {
        uint32_t a[4];
#pragma unroll
        for (int jj = 0; jj < 4; jj++) a[jj] = va[jj] + s * kSlotBytes;
        asm volatile("" : "+r"(a[0]), "+r"(a[1]), "+r"(a[2]), "+r"(a[3]));
        mbar_wait(full + s * 8, parity);
        landed();
#pragma unroll
        for (int j = 0; j < 8; j++) {
            uint32_t r[4];
            ldsm4t(r, a[j & 3] + (j >> 2) * kHalf);
            mma16816(acc[j], r[0], r[1], r[2], r[3], b0, b1);
        }
    };

    uint32_t fifo[kLead + 1][2];
#pragma unroll
    for (int x = 0; x <= kLead; x++) fifo[x][0] = fifo[x][1] = 0u;
    int s = 0, ph = 0;
#pragma unroll 1
    for (int n = -kLead;; n++) {
#pragma unroll
        for (int x = 0; x < kLead; x++) { fifo[x][0] = fifo[x + 1][0]; fifo[x][1] = fifo[x + 1][1]; }
        {
            uint32_t a0 = ka0 + s * kSlotBytes, a1 = ka1 + s * kSlotBytes;
            asm volatile("" : "+r"(a0), "+r"(a1));
            mbar_wait(full + s * 8, ph);
            landed();
            float sc[2][2][4];
#pragma unroll
            for (int u = 0; u < 2; u++)
#pragma unroll
                for (int c = 0; c < 2; c++) sc[u][c][0] = sc[u][c][1] = sc[u][c][2] = sc[u][c][3] = 0.f;
#pragma unroll
            for (int qd = 0; qd < 4; qd++) {
#pragma unroll
                for (int u = 0; u < 2; u++) {
                    uint32_t r[4];
                    ldsm4(r, ((qd & 1) ? a1 : a0) + u * 1024 + (qd >> 1) * kHalf);
                    mma16816(sc[u][0], qa[2 * qd][0], 0u, qa[2 * qd][1], 0u, r[0], r[1]);
                    mma16816(sc[u][1], qa[2 * qd + 1][0], 0u, qa[2 * qd + 1][1], 0u, r[2], r[3]);
                }
            }
            release(s);
            if (++s == kNS) { s = 0; ph ^= 1; }
            const uint32_t s01 = scale_scores(sc[0][0][0] + sc[0][1][0], sc[0][0][1] + sc[0][1][1]);
            const uint32_t s23 = scale_scores(sc[1][0][0] + sc[1][1][0], sc[1][0][1] + sc[1][1][1]);
            fifo[kLead][0] = s01; fifo[kLead][1] = s23;
            float mx = fmaxf(fmaxf(bf_lo(s01), bf_hi(s01)), fmaxf(bf_lo(s23), bf_hi(s23)));
            mx = fmaxf(mx, __shfl_xor_sync(0xffffffffu, mx, 1));
            mx = fmaxf(mx, __shfl_xor_sync(0xffffffffu, mx, 2));
            if (__any_sync(0xffffffffu, mx > m)) {
                const float mn = fmaxf(m, mx);
                const float f = expdiff(m, mn), fo = __shfl_xor_sync(0xffffffffu, f, 4);
                const float f0 = (g & 1) ? fo : f, f1 = (g & 1) ? f : fo;
                m = mn; l *= f;
#pragma unroll
                for (int j = 0; j < 8; j++) { acc[j][0] *= f0; acc[j][1] *= f1; acc[j][2] *= f0; acc[j][3] *= f1; }
            }
        }
        if (n == kNT - kLead - 1) break;
        if (n >= 0) {
            probs(fifo[0][0], fifo[0][1]);
            pv(s, ph, fifo[0][0], fifo[0][1]);
            release(s);
            if (++s == kNS) { s = 0; ph ^= 1; }
        }
    }

    float f0[kNW], f1[kNW], sM0 = -INFINITY, sM1 = -INFINITY, sL0 = 0.f, sL1 = 0.f;
    {
        uint64_t* ob = outbox((split + 1 + (g >> 1)) & 3);
#pragma unroll
        for (int u = 0; u < kFin; u++) {
            const int wd = (u * kNW + warp) * 8 + (g & 1) * 4 + t;
            if ((g >> 1) < 3) st_word(ob + kSecScore + wd, make_word(fifo[kEarly + u][0], fifo[kEarly + u][1]));
            else sts2(aux + kOffP + split * 1024 + wd * 8, fifo[kEarly + u][0], fifo[kEarly + u][1]);
        }
#pragma unroll
        for (int x = 0; x <= kLead; x++) probs(fifo[x][0], fifo[x][1]);
        float lr = l + __shfl_xor_sync(0xffffffffu, l, 1);
        lr += __shfl_xor_sync(0xffffffffu, lr, 2);
        if (t == 0 && g < 2) sts2(aux + kOffMl + warp * 16 + g * 8, __float_as_uint(m), __float_as_uint(lr));
        bar_sync<2, kNC>();
        float mm[kNW][4];
#pragma unroll
        for (int w = 0; w < kNW; w++) {
            lds4(mm[w], aux + kOffMl + w * 16);
            sM0 = fmaxf(sM0, mm[w][0]); sM1 = fmaxf(sM1, mm[w][2]);
        }
#pragma unroll
        for (int w = 0; w < kNW; w++) {
            f0[w] = expdiff(mm[w][0], sM0); f1[w] = expdiff(mm[w][2], sM1);
            sL0 = fmaf(f0[w], mm[w][1], sL0); sL1 = fmaf(f1[w], mm[w][3], sL1);
        }
        if (warp == 0 && (g >> 1) < 3 && !(g & 1))
            st_word(ob + kSecStat + t, (t & 1) ? make_word(sL0, sL1) : make_word(sM0, sM1));
    }

    uint64_t sw[3] = {0ull, 0ull, 0ull}, wm[3] = {0ull, 0ull, 0ull}, wl[3] = {0ull, 0ull, 0ull};
#pragma unroll
    for (int x = 0; x < kEarly; x++) {
        const int i = kNL - 1 - kLead + x;
        if (x == kEarly - 3) {
#pragma unroll
            for (int y = 0; y < 3; y++) {
                ld_word_if(sw[y], inbox + y * kSecWords + kSecScore + tid, true);
                ld_word2_if(wm[y], wl[y], inbox + y * kSecWords + kSecStat, true);
            }
        }
        pv(i % kNS, (i / kNS) & 1, fifo[x][0], fifo[x][1]);
        if (i + kNS < kNL) release(i % kNS);
    }

    if (t == 0) {
#pragma unroll
        for (int j = 0; j < 8; j++) sts4(aux + kOffAcc + warp * 1024 + j * 128 + g * 16, acc[j]);
    }
    bar_sync<2, kNC>();
    if (warp != split) {
        float o0 = 0.f, o1 = 0.f;
#pragma unroll
        for (int w = 0; w < kNW; w++) {
            uint32_t a0, a1;
            lds2(a0, a1, aux + kOffAcc + w * 1024 + (tid >> 4) * 128 + (tid & 7) * 16 + ((tid >> 3) & 1) * 8);
            o0 = fmaf(f0[w], __uint_as_float(a0), o0); o1 = fmaf(f1[w], __uint_as_float(a1), o1);
        }
        st_word(outbox(warp) + kSecOut + lane, make_word(o0 * rcp(sL0), o1 * rcp(sL1)));
    }

#pragma unroll 1
    for (int it = 0;; it++) {
        bool ms[3], mt[3];
#pragma unroll
        for (int y = 0; y < 3; y++) { ms[y] = missing(sw[y]); mt[y] = missing(wm[y]) || missing(wl[y]); }
        if (!(ms[0] || ms[1] || ms[2] || mt[0] || mt[1] || mt[2])) break;
        if (it > (1 << 22)) __trap();
#pragma unroll
        for (int y = 0; y < 3; y++) {
            ld_word_if(sw[y], inbox + y * kSecWords + kSecScore + tid, ms[y]);
            ld_word2_if(wm[y], wl[y], inbox + y * kSecWords + kSecStat, mt[y]);
        }
    }
    __syncwarp();
    float wy[3];
    {
        const float M0 = fmaxf(fmaxf(sM0, word_lo(wm[0])), fmaxf(word_lo(wm[1]), word_lo(wm[2])));
        const float M1 = fmaxf(fmaxf(sM1, word_hi(wm[0])), fmaxf(word_hi(wm[1]), word_hi(wm[2])));
        float c0[3], c1[3];
#pragma unroll
        for (int y = 0; y < 3; y++) {
            c0[y] = expdiff(word_lo(wm[y]), M0) * word_lo(wl[y]);
            c1[y] = expdiff(word_hi(wm[y]), M1) * word_hi(wl[y]);
        }
        const float e0 = expdiff(sM0, M0), e1 = expdiff(sM1, M1);
        const float r0 = rcp((c0[0] + c0[2]) + (c0[1] + e0 * sL0)), r1 = rcp((c1[0] + c1[2]) + (c1[1] + e1 * sL1));
#pragma unroll
        for (int y = 0; y < 3; y++) wy[y] = (t & 1) ? c1[y] * r1 : c0[y] * r0;
#pragma unroll
        for (int w = 0; w < kNW; w++) { f0[w] *= e0 * r0; f1[w] *= e1 * r1; }
        const float Mh = (tid & 4) ? M1 : M0, rh = (tid & 4) ? r1 : r0;
#pragma unroll
        for (int y = 0; y < kSplit; y++) {
            const uint32_t pa = aux + kOffP + ((split + 1 + y) & 3) * 1024 + tid * 8;
            uint32_t s01, s23;
            if (y < 3) {
                s01 = (uint32_t)sw[y]; s23 = (uint32_t)(sw[y] >> 32);
                st_word(inbox + y * kSecWords + kSecScore + tid, 0ull);
            } else {
                lds2(s01, s23, pa);
            }
            sts2(pa, pack_bf16(expdiff(bf_lo(s01), Mh) * rh, expdiff(bf_hi(s01), Mh) * rh),
                     pack_bf16(expdiff(bf_lo(s23), Mh) * rh, expdiff(bf_hi(s23), Mh) * rh));
        }
    }
    bar_sync<2, kNC>();
    if (warp == 3 && lane < 12) st_word(inbox + (lane >> 2) * kSecWords + kSecStat + (lane & 3), 0ull);
    if (warp >= 2) return;

    float c[4][4];
#pragma unroll
    for (int k = 0; k < 4; k++) c[k][0] = c[k][1] = c[k][2] = c[k][3] = 0.f;
#pragma unroll
    for (int w = 0; w < kNW; w++) {
        float v[4];
        lds4(v, aux + kOffAcc + w * 1024 + (split * 2 + warp) * 128 + g * 16);
        c[0][0] = fmaf(f0[w], v[0], c[0][0]); c[0][1] = fmaf(f1[w], v[1], c[0][1]);
        c[0][2] = fmaf(f0[w], v[2], c[0][2]); c[0][3] = fmaf(f1[w], v[3], c[0][3]);
    }
    uint32_t la = sbase + (uint32_t)((mi >> 1) * 8 + r7) * 64 + (((warp * 2 + (mi & 1)) ^ (r7 >> 1)) << 4);
    uint64_t* oin = inbox + kSecOut + warp * 16 + (t >> 1) * 8 + g;
    uint64_t ow[3] = {0ull, 0ull, 0ull};
    bool late = false;
    asm volatile("" : "+r"(la), "+l"(oin), "+l"(ow[0]), "+l"(ow[1]), "+l"(ow[2]));
#pragma unroll
    for (int x = 0; x < kSplit; x++) {
        const int i = kNL - kFin + x;
        uint32_t pb[16][2];
#pragma unroll
        for (int k = 0; k < 16; k++) lds2(pb[k][0], pb[k][1], aux + kOffP + x * 1024 + k * 64 + (g & 1) * 32 + t * 8);
        if (x == kSplit - 1) {
#pragma unroll
            for (int y = 0; y < 3; y++) ld_word_if(ow[y], oin + y * kSecWords, true);
        }
        mbar_wait(full + (i % kNS) * 8, (i / kNS) & 1);
#pragma unroll
        for (int k = 0; k < 16; k++) {
            uint32_t r[4];
            ldsm4t(r, la + (i % kNS) * kSlotBytes + k * 1024);
            mma16816(c[k & 3], r[0], r[1], r[2], r[3], pb[k][0], pb[k][1]);
            if (x == kSplit - 1 && k == 4) {
                late = __any_sync(0xffffffffu, missing(ow[0]) || missing(ow[1]) || missing(ow[2]));
#pragma unroll
                for (int y = 0; y < 3; y++) clear_word_if(oin + y * kSecWords, !late && !(t & 1));
            }
        }
    }
    const uint32_t t1 = t & 1, t2 = t & 2;
    const float o = (sel(t2, sel(t1, c[0][3], c[0][2]), sel(t1, c[0][1], c[0][0])) + sel(t2, sel(t1, c[1][3], c[1][2]), sel(t1, c[1][1], c[1][0])))
                  + (sel(t2, sel(t1, c[2][3], c[2][2]), sel(t1, c[2][1], c[2][0])) + sel(t2, sel(t1, c[3][3], c[3][2]), sel(t1, c[3][1], c[3][0])));
    auto remote = [&]() {
        return fmaf(wy[0], sel(t1, word_hi(ow[0]), word_lo(ow[0])),
               fmaf(wy[1], sel(t1, word_hi(ow[1]), word_lo(ow[1])), wy[2] * sel(t1, word_hi(ow[2]), word_lo(ow[2]))));
    };
    st_bf16_if(op, o + remote(), !late);
    if (late) {
#pragma unroll 1
        for (int it = 0; missing(ow[0]) || missing(ow[1]) || missing(ow[2]); it++) {
            if (it > (1 << 22)) __trap();
#pragma unroll
            for (int y = 0; y < 3; y++) ld_word_if(ow[y], oin + y * kSecWords, missing(ow[y]));
        }
        st_bf16_if(op, o + remote(), true);
        __syncwarp();
#pragma unroll
        for (int y = 0; y < 3; y++) clear_word_if(oin + y * kSecWords, !t1);
    }
}

typedef CUresult (*EncodeTiledFn)(CUtensorMap*, CUtensorMapDataType, cuuint32_t, void*, const cuuint64_t*, const cuuint64_t*,
                                  const cuuint32_t*, const cuuint32_t*, CUtensorMapInterleave, CUtensorMapSwizzle,
                                  CUtensorMapL2promotion, CUtensorMapFloatOOBfill);

CUtensorMap make_tile_map(EncodeTiledFn encode, void* base, uint64_t array_stride) {
    CUtensorMap m;
    const cuuint64_t dims[4] = {64, (cuuint64_t)kPairs * kC, 2, array_stride ? 2u : 1u};
    const cuuint64_t strides[3] = {256, 128, array_stride ? array_stride : (uint64_t)kPairs * kC * 256};
    const cuuint32_t box[4] = {64, (cuuint32_t)kTile, 2, 1};
    const cuuint32_t elem[4] = {1, 1, 1, 1};
    encode(&m, CU_TENSOR_MAP_DATA_TYPE_BFLOAT16, 4, base, dims, strides, box, elem, CU_TENSOR_MAP_INTERLEAVE_NONE,
           CU_TENSOR_MAP_SWIZZLE_128B, CU_TENSOR_MAP_L2_PROMOTION_L2_256B, CU_TENSOR_MAP_FLOAT_OOB_FILL_NONE);
    return m;
}

CUtensorMap make_strip_map(EncodeTiledFn encode, void* base) {
    CUtensorMap m;
    const cuuint64_t dims[2] = {(cuuint64_t)kD, (cuuint64_t)kPairs * kC};
    const cuuint64_t strides[1] = {256};
    const cuuint32_t box[2] = {32, (cuuint32_t)(kFin * kTile)};
    const cuuint32_t elem[2] = {1, 1};
    encode(&m, CU_TENSOR_MAP_DATA_TYPE_BFLOAT16, 2, base, dims, strides, box, elem, CU_TENSOR_MAP_INTERLEAVE_NONE,
           CU_TENSOR_MAP_SWIZZLE_64B, CU_TENSOR_MAP_L2_PROMOTION_L2_256B, CU_TENSOR_MAP_FLOAT_OOB_FILL_NONE);
    return m;
}

template <class Maps>
void launch(const Maps& maps, int k_index, void* const* d_in, void* d_out, void* inboxes, Pace pace) {
    tree_attn_decode_kernel<Maps><<<kPairs * kSplit, kThreads, kSmemBytes>>>(
        (const __nv_bfloat16*)d_in[1], (const __nv_bfloat16*)d_in[0], (const __nv_bfloat16*)d_in[3], (const __nv_bfloat16*)d_in[4],
        (const __nv_bfloat16*)d_in[5], (__nv_bfloat16*)d_out, maps, (uint64_t*)inboxes, pace, k_index);
}

}

extern "C" void kernel_launch(void* const* d_in, const int* in_sizes, int n_in, void* d_out, int out_size) {
    (void)in_sizes; (void)n_in; (void)out_size;
    static EncodeTiledFn encode = nullptr;
    static void* inboxes = nullptr;
    static Pace pace = {0, 0, 0, 0};
    if (!encode) {
        cudaDriverEntryPointQueryResult qr;
        cudaGetDriverEntryPoint("cuTensorMapEncodeTiled", (void**)&encode, cudaEnableDefault, &qr);
        cudaFuncSetAttribute(tree_attn_decode_kernel<OneMap>, cudaFuncAttributeMaxDynamicSharedMemorySize, kSmemBytes);
        cudaFuncSetAttribute(tree_attn_decode_kernel<TwoMaps>, cudaFuncAttributeMaxDynamicSharedMemorySize, kSmemBytes);
        cudaGetSymbolAddress(&inboxes, g_inbox);
        int dev = 0, mem_khz = 0, bus_bits = 0;
        cudaGetDevice(&dev);
        cudaDeviceGetAttribute(&mem_khz, cudaDevAttrMemoryClockRate, dev);
        cudaDeviceGetAttribute(&bus_bits, cudaDevAttrGlobalMemoryBusWidth, dev);
        const double bytes_per_ns = 2.0 * mem_khz * 1e-6 * bus_bits / 8.0;
        if (bytes_per_ns > 0.0) {
            const double tau = (double)kPairs * kSplit * kSlotBytes / (0.9595 * bytes_per_ns);
            pace = {(int)(2.0 * tau), (int)(tau * 256.0), (int)(4.14 * tau), (int)(1.02 * tau * 256.0)};
        }
    }
    const uintptr_t k = (uintptr_t)d_in[1], v = (uintptr_t)d_in[2];
    const uint64_t dist = k < v ? v - k : k - v;
    if (dist != 0 && dist % 16 == 0 && dist < (1ull << 40)) {
        launch(OneMap{make_tile_map(encode, k < v ? d_in[1] : d_in[2], dist), make_strip_map(encode, d_in[2])},
               k < v ? 0 : 1, d_in, d_out, inboxes, pace);
    } else {
        launch(TwoMaps{make_tile_map(encode, d_in[1], 0), make_tile_map(encode, d_in[2], 0), make_strip_map(encode, d_in[2])},
               0, d_in, d_out, inboxes, pace);
    }
}
```
